```python
import torch

def _softmax(x, axis=-1):
    return torch.softmax(x, dim=axis)

def _gelu(x):
    return torch.nn.functional.gelu(x, approximate='tanh')

def _silu(x):
    return torch.nn.functional.silu(x)

def _sigmoid(x):
    return torch.sigmoid(x)

def _layernorm(x, axis=-1, eps=1e-05):
    m = x.mean(dim=axis, keepdim=True)
    v = x.var(dim=axis, keepdim=True, unbiased=False)
    return (x - m) / torch.sqrt(v + eps)

def _scatter_add(tgt, idx, src, axis=0):
    return tgt.clone().index_add_(axis, idx, src)

def _segment_sum(src, seg, n):
    out = torch.zeros((n,) + src.shape[1:], dtype=src.dtype)
    return out.index_add_(0, seg, src)

def _pad(x, pw):
    flat = tuple((v for pair in reversed(pw) for v in pair))
    return torch.nn.functional.pad(x, flat)
kernel_name = 'adaLN_cond__sliding_block__glu_gated_bilinear__prompt'

def setup_inputs():

    _w = lambda a: (lambda t: t.to(torch.bfloat16) if t.is_floating_point() else t)(torch.as_tensor(a))

    def _A_setup():
        B, S, D = (1, 2048, 512)
        return {'x': _w((lambda *s: torch.randn(*s, dtype=torch.bfloat16) * 0.05)(B, S, D)), 'wqkv': _w((lambda *s: torch.randn(*s, dtype=torch.bfloat16) * 0.05)(D, 3 * D)), 'wo': _w((lambda *s: torch.randn(*s, dtype=torch.bfloat16) * 0.05)(D, D))}
    _A_in = _A_setup()

    def _B_setup():
        B, S, D, F = (1, 2048, 512, 1376)
        return {'x': _w((lambda *s: torch.randn(*s, dtype=torch.bfloat16) * 0.05)(B, S, D)), 'w_gate': _w((lambda *s: torch.randn(*s, dtype=torch.bfloat16) * 0.8)(D, F) * D ** (-0.5)), 'w_up': _w((lambda *s: torch.randn(*s, dtype=torch.bfloat16) * 0.8)(D, F) * D ** (-0.5)), 'w_down': _w((lambda *s: torch.randn(*s, dtype=torch.bfloat16) * 0.8)(F, D) * F ** (-0.5))}
    _B_in = _B_setup()
    return {'A_x': _A_in['x'], 'A_wqkv': _A_in['wqkv'], 'A_wo': _A_in['wo'], 'B_x': _B_in['x'], 'B_w_gate': _B_in['w_gate'], 'B_w_up': _B_in['w_up'], 'B_w_down': _B_in['w_down'], 'c': _w((lambda *s: torch.randn(*s, dtype=torch.bfloat16) * 0.1)(1, 512) * 8.0), 'w_mod': _w((lambda *s: torch.randn(*s, dtype=torch.bfloat16) * 0.1)(512, 6 * 512) * 512 ** (-0.5) * 8.0)}

def reference(A_x, A_wqkv, A_wo, B_x, B_w_gate, B_w_up, B_w_down, c, w_mod):

    def _A_ref(x, wqkv, wo):
        B, S, D = x.shape
        H = 32
        Dh = D // H
        W = 256
        qkv = (lambda x, *d: x.permute(*d))((x @ wqkv).reshape(B, S, 3, H, Dh), 2, 0, 3, 1, 4)
        q, k, v = (qkv[0], qkv[1], qkv[2])
        scores = torch.einsum('bhqd,bhkd->bhqk', q, k) * Dh ** (-0.5)
        idx = torch.arange(S)
        mask = (idx[:, None] - idx[None, :] >= 0) & (idx[:, None] - idx[None, :] < W)
        scores = torch.where(mask[None, None], scores, -1000000000.0)
        p = _softmax(scores, axis=-1)
        o = torch.einsum('bhqk,bhkd->bhqd', p, v)
        return (lambda x, *d: x.permute(*d))(o, 0, 2, 1, 3).reshape(B, S, D) @ wo

    def _B_ref(x, w_gate, w_up, w_down):
        g = torch.einsum('bsd,df->bsf', x, w_gate)
        u = torch.einsum('bsd,df->bsf', x, w_up)
        h = g * u
        return torch.einsum('bsf,fd->bsd', h, w_down)
    x = A_x
    mod = (_silu(c) @ w_mod).reshape(c.shape[0], 6, 1, -1)
    sa, ca, ga, sb, cb, gb = (mod[:, 0].clone(), mod[:, 1].clone(), mod[:, 2].clone(), mod[:, 3].clone(), mod[:, 4].clone(), mod[:, 5].clone())
    h = _layernorm(x, axis=-1) * (1 + ca) + sa
    x = x + ga * _A_ref(h, A_wqkv, A_wo)
    h = _layernorm(x, axis=-1) * (1 + cb) + sb
    x = x + gb * _B_ref(h, B_w_gate, B_w_up, B_w_down)
    return x
```

```cpp
#include <cuda_runtime.h>
#include <cuda_bf16.h>
#include <cuda.h>
#include <stdint.h>

#define NORM3 0
#define REL_H 3
#define O3_H 2
#define H2_WAIT 200
#define INFL 2
namespace {

constexpr int kD = 512, kF = 1376;
constexpr int kThreads = 384;
constexpr int kCtas = 128;

constexpr uint32_t U = 8192;
constexpr uint32_t OFF_K = 0;
constexpr uint32_t OFF_V = 6 * U;
constexpr uint32_t OFF_WV = 12 * U;
constexpr uint32_t OFF_WQ = 20 * U;
constexpr uint32_t STAGE = 4 * U;
constexpr uint32_t OFF_RED = 2 * STAGE;
constexpr uint32_t OFF_MISC = 28 * U;
constexpr uint32_t OFF_BAR = OFF_MISC;
constexpr uint32_t OFF_TMP = OFF_MISC + 512;
constexpr uint32_t OFF_TAB = OFF_MISC + 1024;
constexpr uint32_t SMEM_BYTES = OFF_MISC + 3072;

enum {
  B_X = 0  , B_WKV = 4  ,
  B_WO = 10, B_RED = 11  ,
  B_TAB = 13,
  B_KRDY = 14, B_KN = 15, B_VN = 16,
  B_XFREE = 17,
  B_FULL = 18  ,
  B_EMPTY = 25  ,
  B_COUNT = 32
};
__host__ __device__ constexpr uint32_t kv_off(int c) { return c == 0 ? 4 * U : (c == 1 ? 0 : (c == 2 ? 6 * U : OFF_WV)); }
__host__ __device__ constexpr uint32_t kv_lbo(int c) { return c == 0 ? 6 * U : 2 * U; }

__host__ __device__ constexpr int ring_slot(int t) { return (0x431065 >> (4 * (t % 6))) & 7; }
__host__ __device__ constexpr int dn_step(int t, int e) { return 11 * (2 * (t & 1) + (e >> 2)) + 4 * (t >> 1) + (e & 3); }

struct Scratch {
  uint4 o[128 * 32 * 32];
  uint4 h2[128 * 32 * 32];
  uint4 hh[128 * 86 * 32];
  uint4 kv[kCtas * 2 * 1024];
  float mod1[8][1024];
  float mod2[8][2048];
  uint4 xres[128 * 32 * 32];
  uint4 st2[8][2048];
  unsigned epoch[2 * kCtas * 32];
};
__device__ Scratch g_s;
#define FINE(t, i) do {} while (0)
#define FINE2(i) do {} while (0)

struct Params {
  CUtensorMap tm_x, tm_qkv, tm_wo, tm_g0, tm_g1, tm_u0, tm_u1, tm_wd;
  const __nv_bfloat16 *wo, *wg, *wu, *wd;
};

constexpr int kSpinLimit = 1 << 13;

__device__ __forceinline__ void mbar_init(uint32_t b, int cnt) { asm volatile("mbarrier.init.shared::cta.b64 [%0], %1;" ::"r"(b), "r"(cnt) : "memory"); }
__device__ __forceinline__ void mbar_expect(uint32_t b, uint32_t bytes) { asm volatile("mbarrier.arrive.expect_tx.shared::cta.b64 _, [%0], %1;" ::"r"(b), "r"(bytes) : "memory"); }
__device__ __forceinline__ void mbar_arrive(uint32_t b) { asm volatile("mbarrier.arrive.shared::cta.b64 _, [%0];" ::"r"(b) : "memory"); }
__device__ __forceinline__ void mbar_wait(uint32_t b, uint32_t ph) {
  asm volatile("{\n.reg .pred p;\n.reg .u32 n;\nmov.u32 n, 0;\n"
               "W: mbarrier.try_wait.parity.shared::cta.b64 p, [%0], %1;\n@p bra D;\n"
               "add.u32 n, n, 1;\nsetp.lt.u32 p, n, 8192;\n@p bra W;\nD:\n}" ::"r"(b), "r"(ph) : "memory");
}
__device__ __forceinline__ void mbar_wait_cluster(uint32_t b, uint32_t ph) {
  asm volatile("{\n.reg .pred p;\n.reg .u32 n;\nmov.u32 n, 0;\n"
               "W: mbarrier.try_wait.parity.acquire.cluster.shared::cta.b64 p, [%0], %1;\n@p bra D;\n"
               "add.u32 n, n, 1;\nsetp.lt.u32 p, n, 8192;\n@p bra W;\nD:\n}" ::"r"(b), "r"(ph) : "memory");
}
__device__ __forceinline__ void bar_sync(int id, int n) { asm volatile("bar.sync %0, %1;" ::"r"(id), "r"(n) : "memory"); }
__device__ __forceinline__ void bar_arrive(int id, int n) { asm volatile("bar.arrive %0, %1;" ::"r"(id), "r"(n) : "memory"); }
__device__ __forceinline__ unsigned next_tag(unsigned e) { unsigned t; asm volatile("add.u32 %0, %1, 1;" : "=r"(t) : "r"(e) : "memory"); return t; }
__device__ __forceinline__ void fence_async_smem() { asm volatile("fence.proxy.async.shared::cta;" ::: "memory"); }
__device__ __forceinline__ void tma2d(uint32_t dst, const CUtensorMap* tm, int c0, int c1, uint32_t bar) {
  asm volatile("cp.async.bulk.tensor.2d.shared::cluster.global.mbarrier::complete_tx::bytes [%0], [%1, {%3, %4}], [%2];"
               ::"r"(dst), "l"(tm), "r"(bar), "r"(c0), "r"(c1) : "memory");
}
__device__ __forceinline__ void tma2d_mc(uint32_t dst, const CUtensorMap* tm, int c0, int c1, uint32_t bar) {
  asm volatile("cp.async.bulk.tensor.2d.shared::cluster.global.mbarrier::complete_tx::bytes.multicast::cluster [%0], [%1, {%3, %4}], [%2], %5;"
               ::"r"(dst), "l"(tm), "r"(bar), "r"(c0), "r"(c1), "h"((uint16_t)3) : "memory");
}
__device__ __forceinline__ void tma3d_mc(uint32_t dst, const CUtensorMap* tm, int c0, int c1, int c2, uint32_t bar) {
  asm volatile("cp.async.bulk.tensor.3d.shared::cluster.global.mbarrier::complete_tx::bytes.multicast::cluster [%0], [%1, {%3, %4, %5}], [%2], %6;"
               ::"r"(dst), "l"(tm), "r"(bar), "r"(c0), "r"(c1), "r"(c2), "h"((uint16_t)3) : "memory");
}
__device__ __forceinline__ void l2_prefetch(const void* p, uint32_t bytes) { asm volatile("cp.async.bulk.prefetch.L2.global [%0], %1;" ::"l"(p), "r"(bytes) : "memory"); }
__device__ __forceinline__ uint4 ld_try(const uint4* p) {
  uint4 v;
  asm volatile("ld.global.v4.u32 {%0,%1,%2,%3}, [%4];" : "=r"(v.x), "=r"(v.y), "=r"(v.z), "=r"(v.w) : "l"(p) : "memory");
  return v;
}
__device__ __forceinline__ void st_tag(unsigned tag, uint4* p, uint4 v) {
  asm volatile("{\n.reg .b64 lo, hi;\n.reg .b128 v;\n.reg .b32 w;\nlop3.b32 w, %4, %5, 1, 0xD8;\n"
               "mov.b64 lo, {%1, %2};\nmov.b64 hi, {%3, w};\nmov.b128 v, {lo, hi};\nst.relaxed.gpu.global.b128 [%0], v;\n}"
               ::"l"(p), "r"(v.x), "r"(v.y), "r"(v.z), "r"(v.w), "r"(tag) : "memory");
}
__device__ __forceinline__ ulonglong2 ld_rlx2(const void* p) {
  ulonglong2 v;
  asm volatile("ld.relaxed.gpu.global.v2.b64 {%0,%1}, [%2];" : "=l"(v.x), "=l"(v.y) : "l"(p) : "memory");
  return v;
}
__device__ __forceinline__ void st_rlx2(void* p, unsigned long long a, unsigned long long b) {
  asm volatile("st.relaxed.gpu.global.v2.b64 [%0], {%1,%2};" ::"l"(p), "l"(a), "l"(b) : "memory");
}
__device__ __forceinline__ unsigned clock32() { unsigned c; asm volatile("mov.u32 %0, %%clock;" : "=r"(c)); return c; }
__device__ __forceinline__ uint4 ldg128(const void* p) {
  uint4 v;
  asm volatile("ld.global.nc.v4.u32 {%0,%1,%2,%3}, [%4];" : "=r"(v.x), "=r"(v.y), "=r"(v.z), "=r"(v.w) : "l"(p));
  return v;
}
__device__ __forceinline__ uint4 lds128(uint32_t a) {
  uint4 v;
  asm volatile("ld.shared.v4.u32 {%0,%1,%2,%3}, [%4];" : "=r"(v.x), "=r"(v.y), "=r"(v.z), "=r"(v.w) : "r"(a));
  return v;
}
__device__ __forceinline__ uint32_t lds32(uint32_t a) { uint32_t v; asm volatile("ld.shared.u32 %0, [%1];" : "=r"(v) : "r"(a)); return v; }
__device__ __forceinline__ void sts32(uint32_t a, uint32_t v) { asm volatile("st.shared.u32 [%0], %1;" ::"r"(a), "r"(v) : "memory"); }
__device__ __forceinline__ void sts128f(uint32_t a, float x, float y, float z, float w) {
  asm volatile("st.shared.v4.f32 [%0], {%1,%2,%3,%4};" ::"r"(a), "f"(x), "f"(y), "f"(z), "f"(w) : "memory");
}
__device__ __forceinline__ void ldsm4(uint32_t (&r)[4], uint32_t a) {
  asm volatile("ldmatrix.sync.aligned.m8n8.x4.shared.b16 {%0,%1,%2,%3}, [%4];" : "=r"(r[0]), "=r"(r[1]), "=r"(r[2]), "=r"(r[3]) : "r"(a));
}
__device__ __forceinline__ void ldsm4t(uint32_t (&r)[4], uint32_t a) {
  asm volatile("ldmatrix.sync.aligned.m8n8.x4.trans.shared.b16 {%0,%1,%2,%3}, [%4];" : "=r"(r[0]), "=r"(r[1]), "=r"(r[2]), "=r"(r[3]) : "r"(a));
}
__device__ __forceinline__ void stsm4(uint32_t a, uint32_t r0, uint32_t r1, uint32_t r2, uint32_t r3) {
  asm volatile("stmatrix.sync.aligned.m8n8.x4.shared.b16 [%0], {%1,%2,%3,%4};" ::"r"(a), "r"(r0), "r"(r1), "r"(r2), "r"(r3) : "memory");
}
__device__ __forceinline__ void mma16816(float* d, uint32_t a0, uint32_t a1, uint32_t a2, uint32_t a3, uint32_t b0, uint32_t b1) {
  asm("mma.sync.aligned.m16n8k16.row.col.f32.bf16.bf16.f32 {%0,%1,%2,%3}, {%4,%5,%6,%7}, {%8,%9}, {%0,%1,%2,%3};"
      : "+f"(d[0]), "+f"(d[1]), "+f"(d[2]), "+f"(d[3]) : "r"(a0), "r"(a1), "r"(a2), "r"(a3), "r"(b0), "r"(b1));
}
__device__ __forceinline__ void mma16816_z(float* d, uint32_t a0, uint32_t a1, uint32_t a2, uint32_t a3, uint32_t b0, uint32_t b1) {
  asm("mma.sync.aligned.m16n8k16.row.col.f32.bf16.bf16.f32 {%0,%1,%2,%3}, {%4,%5,%6,%7}, {%8,%9}, {%10,%10,%10,%10};"
      : "=f"(d[0]), "=f"(d[1]), "=f"(d[2]), "=f"(d[3]) : "r"(a0), "r"(a1), "r"(a2), "r"(a3), "r"(b0), "r"(b1), "f"(0.f));
}
__device__ __forceinline__ uint32_t pack2(float lo, float hi) { uint32_t r; asm("cvt.rn.bf16x2.f32 %0, %1, %2;" : "=r"(r) : "f"(hi), "f"(lo)); return r; }
__device__ __forceinline__ float bf_lo(uint32_t w) { return __uint_as_float(w << 16); }
__device__ __forceinline__ float bf_hi(uint32_t w) { return __uint_as_float(w & 0xFFFF0000u); }
__device__ __forceinline__ float bf_round(float x) { return __bfloat162float(__float2bfloat16_rn(x)); }
__device__ __forceinline__ uint32_t hfma2(uint32_t a, uint32_t b, uint32_t c) { uint32_t r; asm("fma.rn.bf16x2 %0, %1, %2, %3;" : "=r"(r) : "r"(a), "r"(b), "r"(c)); return r; }
__device__ __forceinline__ float ex2(float x) { float y; asm("ex2.approx.ftz.f32 %0, %1;" : "=f"(y) : "f"(x)); return y; }
struct RowNorm { uint32_t hi, c; };
__device__ __forceinline__ RowNorm make_norm(float mean, float rstd) {
  RowNorm n;
  const float h = bf_round(rstd);
  n.hi = pack2(h, h);
  n.c = pack2(-mean * h, -mean * h);
  return n;
}
__device__ __forceinline__ uint32_t norm1(uint32_t w, const RowNorm& n) { return hfma2(w, n.hi, n.c); }
__device__ __forceinline__ uint64_t mkdesc(uint32_t lo) {
  uint64_t d;
  asm("mov.b64 %0, {%1, %2};" : "=l"(d) : "r"(lo), "r"(0x40000040u));
  return d;
}
__device__ __forceinline__ void wg_fence() { asm volatile("wgmma.fence.sync.aligned;" ::: "memory"); }
__device__ __forceinline__ void wg_commit() { asm volatile("wgmma.commit_group.sync.aligned;" ::: "memory"); }
template <int N> __device__ __forceinline__ void wg_wait() { asm volatile("wgmma.wait_group.sync.aligned %0;" ::"n"(N) : "memory"); }
template <int N> __device__ __forceinline__ void pin(float (&d)[N]) {
#pragma unroll
  for (int i = 0; i < N; i++) asm volatile("" : "+f"(d[i])::"memory");
}
__device__ __forceinline__ float silu_bf(float c) { return bf_round(__fdividef(c, 1.f + __expf(-c))); }

__device__ __forceinline__ void wgmma_rs_n64_z(float (&d)[32], uint32_t a0, uint32_t a1, uint32_t a2, uint32_t a3, uint64_t desc) {
  asm volatile(
    "wgmma.mma_async.sync.aligned.m64n64k16.f32.bf16.bf16 "
    "{%0, %1, %2, %3, %4, %5, %6, %7, %8, %9, %10, %11, %12, %13, %14, %15, "
    "%16, %17, %18, %19, %20, %21, %22, %23, %24, %25, %26, %27, %28, %29, %30, %31}, "
    "{%32, %33, %34, %35}, %36, 0, 1, 1, 1;"
    : "=f"(d[0]), "=f"(d[1]), "=f"(d[2]), "=f"(d[3]), "=f"(d[4]), "=f"(d[5]), "=f"(d[6]), "=f"(d[7]),
      "=f"(d[8]), "=f"(d[9]), "=f"(d[10]), "=f"(d[11]), "=f"(d[12]), "=f"(d[13]), "=f"(d[14]), "=f"(d[15]),
      "=f"(d[16]), "=f"(d[17]), "=f"(d[18]), "=f"(d[19]), "=f"(d[20]), "=f"(d[21]), "=f"(d[22]), "=f"(d[23]),
      "=f"(d[24]), "=f"(d[25]), "=f"(d[26]), "=f"(d[27]), "=f"(d[28]), "=f"(d[29]), "=f"(d[30]), "=f"(d[31])
    : "r"(a0), "r"(a1), "r"(a2), "r"(a3), "l"(desc));
}

__device__ __forceinline__ void wgmma_rs_n64_a(float (&d)[32], uint32_t a0, uint32_t a1, uint32_t a2, uint32_t a3, uint64_t desc) {
  asm volatile(
    "wgmma.mma_async.sync.aligned.m64n64k16.f32.bf16.bf16 "
    "{%0, %1, %2, %3, %4, %5, %6, %7, %8, %9, %10, %11, %12, %13, %14, %15, "
    "%16, %17, %18, %19, %20, %21, %22, %23, %24, %25, %26, %27, %28, %29, %30, %31}, "
    "{%32, %33, %34, %35}, %36, 1, 1, 1, 1;"
    : "+f"(d[0]), "+f"(d[1]), "+f"(d[2]), "+f"(d[3]), "+f"(d[4]), "+f"(d[5]), "+f"(d[6]), "+f"(d[7]),
      "+f"(d[8]), "+f"(d[9]), "+f"(d[10]), "+f"(d[11]), "+f"(d[12]), "+f"(d[13]), "+f"(d[14]), "+f"(d[15]),
      "+f"(d[16]), "+f"(d[17]), "+f"(d[18]), "+f"(d[19]), "+f"(d[20]), "+f"(d[21]), "+f"(d[22]), "+f"(d[23]),
      "+f"(d[24]), "+f"(d[25]), "+f"(d[26]), "+f"(d[27]), "+f"(d[28]), "+f"(d[29]), "+f"(d[30]), "+f"(d[31])
    : "r"(a0), "r"(a1), "r"(a2), "r"(a3), "l"(desc));
}

__device__ __forceinline__ void wgmma_rs_n64(float (&d)[32], uint32_t a0, uint32_t a1, uint32_t a2, uint32_t a3, uint64_t desc, bool acc) {
  if (acc) wgmma_rs_n64_a(d, a0, a1, a2, a3, desc); else wgmma_rs_n64_z(d, a0, a1, a2, a3, desc);
}

__device__ __forceinline__ void wgmma_rs_n112_z(float (&d)[56], uint32_t a0, uint32_t a1, uint32_t a2, uint32_t a3, uint64_t desc) {
  asm volatile(
    "wgmma.mma_async.sync.aligned.m64n112k16.f32.bf16.bf16 "
    "{%0, %1, %2, %3, %4, %5, %6, %7, %8, %9, %10, %11, %12, %13, %14, %15, "
    "%16, %17, %18, %19, %20, %21, %22, %23, %24, %25, %26, %27, %28, %29, %30, %31, "
    "%32, %33, %34, %35, %36, %37, %38, %39, %40, %41, %42, %43, %44, %45, %46, %47, "
    "%48, %49, %50, %51, %52, %53, %54, %55}, "
    "{%56, %57, %58, %59}, %60, 0, 1, 1, 1;"
    : "=f"(d[0]), "=f"(d[1]), "=f"(d[2]), "=f"(d[3]), "=f"(d[4]), "=f"(d[5]), "=f"(d[6]), "=f"(d[7]),
      "=f"(d[8]), "=f"(d[9]), "=f"(d[10]), "=f"(d[11]), "=f"(d[12]), "=f"(d[13]), "=f"(d[14]), "=f"(d[15]),
      "=f"(d[16]), "=f"(d[17]), "=f"(d[18]), "=f"(d[19]), "=f"(d[20]), "=f"(d[21]), "=f"(d[22]), "=f"(d[23]),
      "=f"(d[24]), "=f"(d[25]), "=f"(d[26]), "=f"(d[27]), "=f"(d[28]), "=f"(d[29]), "=f"(d[30]), "=f"(d[31]),
      "=f"(d[32]), "=f"(d[33]), "=f"(d[34]), "=f"(d[35]), "=f"(d[36]), "=f"(d[37]), "=f"(d[38]), "=f"(d[39]),
      "=f"(d[40]), "=f"(d[41]), "=f"(d[42]), "=f"(d[43]), "=f"(d[44]), "=f"(d[45]), "=f"(d[46]), "=f"(d[47]),
      "=f"(d[48]), "=f"(d[49]), "=f"(d[50]), "=f"(d[51]), "=f"(d[52]), "=f"(d[53]), "=f"(d[54]), "=f"(d[55])
    : "r"(a0), "r"(a1), "r"(a2), "r"(a3), "l"(desc));
}

__device__ __forceinline__ void wgmma_rs_n112_a(float (&d)[56], uint32_t a0, uint32_t a1, uint32_t a2, uint32_t a3, uint64_t desc) {
  asm volatile(
    "wgmma.mma_async.sync.aligned.m64n112k16.f32.bf16.bf16 "
    "{%0, %1, %2, %3, %4, %5, %6, %7, %8, %9, %10, %11, %12, %13, %14, %15, "
    "%16, %17, %18, %19, %20, %21, %22, %23, %24, %25, %26, %27, %28, %29, %30, %31, "
    "%32, %33, %34, %35, %36, %37, %38, %39, %40, %41, %42, %43, %44, %45, %46, %47, "
    "%48, %49, %50, %51, %52, %53, %54, %55}, "
    "{%56, %57, %58, %59}, %60, 1, 1, 1, 1;"
    : "+f"(d[0]), "+f"(d[1]), "+f"(d[2]), "+f"(d[3]), "+f"(d[4]), "+f"(d[5]), "+f"(d[6]), "+f"(d[7]),
      "+f"(d[8]), "+f"(d[9]), "+f"(d[10]), "+f"(d[11]), "+f"(d[12]), "+f"(d[13]), "+f"(d[14]), "+f"(d[15]),
      "+f"(d[16]), "+f"(d[17]), "+f"(d[18]), "+f"(d[19]), "+f"(d[20]), "+f"(d[21]), "+f"(d[22]), "+f"(d[23]),
      "+f"(d[24]), "+f"(d[25]), "+f"(d[26]), "+f"(d[27]), "+f"(d[28]), "+f"(d[29]), "+f"(d[30]), "+f"(d[31]),
      "+f"(d[32]), "+f"(d[33]), "+f"(d[34]), "+f"(d[35]), "+f"(d[36]), "+f"(d[37]), "+f"(d[38]), "+f"(d[39]),
      "+f"(d[40]), "+f"(d[41]), "+f"(d[42]), "+f"(d[43]), "+f"(d[44]), "+f"(d[45]), "+f"(d[46]), "+f"(d[47]),
      "+f"(d[48]), "+f"(d[49]), "+f"(d[50]), "+f"(d[51]), "+f"(d[52]), "+f"(d[53]), "+f"(d[54]), "+f"(d[55])
    : "r"(a0), "r"(a1), "r"(a2), "r"(a3), "l"(desc));
}

__device__ __forceinline__ void wgmma_rs_n112(float (&d)[56], uint32_t a0, uint32_t a1, uint32_t a2, uint32_t a3, uint64_t desc, bool acc) {
  if (acc) wgmma_rs_n112_a(d, a0, a1, a2, a3, desc); else wgmma_rs_n112_z(d, a0, a1, a2, a3, desc);
}

__device__ __forceinline__ void wgmma_rs_n128_z(float (&d)[64], uint32_t a0, uint32_t a1, uint32_t a2, uint32_t a3, uint64_t desc) {
  asm volatile(
    "wgmma.mma_async.sync.aligned.m64n128k16.f32.bf16.bf16 "
    "{%0, %1, %2, %3, %4, %5, %6, %7, %8, %9, %10, %11, %12, %13, %14, %15, "
    "%16, %17, %18, %19, %20, %21, %22, %23, %24, %25, %26, %27, %28, %29, %30, %31, "
    "%32, %33, %34, %35, %36, %37, %38, %39, %40, %41, %42, %43, %44, %45, %46, %47, "
    "%48, %49, %50, %51, %52, %53, %54, %55, %56, %57, %58, %59, %60, %61, %62, %63}, "
    "{%64, %65, %66, %67}, %68, 0, 1, 1, 1;"
    : "=f"(d[0]), "=f"(d[1]), "=f"(d[2]), "=f"(d[3]), "=f"(d[4]), "=f"(d[5]), "=f"(d[6]), "=f"(d[7]),
      "=f"(d[8]), "=f"(d[9]), "=f"(d[10]), "=f"(d[11]), "=f"(d[12]), "=f"(d[13]), "=f"(d[14]), "=f"(d[15]),
      "=f"(d[16]), "=f"(d[17]), "=f"(d[18]), "=f"(d[19]), "=f"(d[20]), "=f"(d[21]), "=f"(d[22]), "=f"(d[23]),
      "=f"(d[24]), "=f"(d[25]), "=f"(d[26]), "=f"(d[27]), "=f"(d[28]), "=f"(d[29]), "=f"(d[30]), "=f"(d[31]),
      "=f"(d[32]), "=f"(d[33]), "=f"(d[34]), "=f"(d[35]), "=f"(d[36]), "=f"(d[37]), "=f"(d[38]), "=f"(d[39]),
      "=f"(d[40]), "=f"(d[41]), "=f"(d[42]), "=f"(d[43]), "=f"(d[44]), "=f"(d[45]), "=f"(d[46]), "=f"(d[47]),
      "=f"(d[48]), "=f"(d[49]), "=f"(d[50]), "=f"(d[51]), "=f"(d[52]), "=f"(d[53]), "=f"(d[54]), "=f"(d[55]),
      "=f"(d[56]), "=f"(d[57]), "=f"(d[58]), "=f"(d[59]), "=f"(d[60]), "=f"(d[61]), "=f"(d[62]), "=f"(d[63])
    : "r"(a0), "r"(a1), "r"(a2), "r"(a3), "l"(desc));
}

__device__ __forceinline__ void wgmma_rs_n128_a(float (&d)[64], uint32_t a0, uint32_t a1, uint32_t a2, uint32_t a3, uint64_t desc) {
  asm volatile(
    "wgmma.mma_async.sync.aligned.m64n128k16.f32.bf16.bf16 "
    "{%0, %1, %2, %3, %4, %5, %6, %7, %8, %9, %10, %11, %12, %13, %14, %15, "
    "%16, %17, %18, %19, %20, %21, %22, %23, %24, %25, %26, %27, %28, %29, %30, %31, "
    "%32, %33, %34, %35, %36, %37, %38, %39, %40, %41, %42, %43, %44, %45, %46, %47, "
    "%48, %49, %50, %51, %52, %53, %54, %55, %56, %57, %58, %59, %60, %61, %62, %63}, "
    "{%64, %65, %66, %67}, %68, 1, 1, 1, 1;"
    : "+f"(d[0]), "+f"(d[1]), "+f"(d[2]), "+f"(d[3]), "+f"(d[4]), "+f"(d[5]), "+f"(d[6]), "+f"(d[7]),
      "+f"(d[8]), "+f"(d[9]), "+f"(d[10]), "+f"(d[11]), "+f"(d[12]), "+f"(d[13]), "+f"(d[14]), "+f"(d[15]),
      "+f"(d[16]), "+f"(d[17]), "+f"(d[18]), "+f"(d[19]), "+f"(d[20]), "+f"(d[21]), "+f"(d[22]), "+f"(d[23]),
      "+f"(d[24]), "+f"(d[25]), "+f"(d[26]), "+f"(d[27]), "+f"(d[28]), "+f"(d[29]), "+f"(d[30]), "+f"(d[31]),
      "+f"(d[32]), "+f"(d[33]), "+f"(d[34]), "+f"(d[35]), "+f"(d[36]), "+f"(d[37]), "+f"(d[38]), "+f"(d[39]),
      "+f"(d[40]), "+f"(d[41]), "+f"(d[42]), "+f"(d[43]), "+f"(d[44]), "+f"(d[45]), "+f"(d[46]), "+f"(d[47]),
      "+f"(d[48]), "+f"(d[49]), "+f"(d[50]), "+f"(d[51]), "+f"(d[52]), "+f"(d[53]), "+f"(d[54]), "+f"(d[55]),
      "+f"(d[56]), "+f"(d[57]), "+f"(d[58]), "+f"(d[59]), "+f"(d[60]), "+f"(d[61]), "+f"(d[62]), "+f"(d[63])
    : "r"(a0), "r"(a1), "r"(a2), "r"(a3), "l"(desc));
}

__device__ __forceinline__ void wgmma_rs_n128(float (&d)[64], uint32_t a0, uint32_t a1, uint32_t a2, uint32_t a3, uint64_t desc, bool acc) {
  if (acc) wgmma_rs_n128_a(d, a0, a1, a2, a3, desc); else wgmma_rs_n128_z(d, a0, a1, a2, a3, desc);
}

__device__ __forceinline__ void arrive_both(uint32_t b, int lane) {
  asm volatile("{\n.reg .pred p;\n.reg .u32 a;\nsetp.lt.u32 p, %1, 2;\n@p mapa.shared::cluster.u32 a, %0, %1;\n"
               "@p mbarrier.arrive.shared::cluster.b64 _, [a];\n}" ::"r"(b), "r"(lane) : "memory");
}
template <int N, int STRIDE> struct Val;
template <int STRIDE> struct Val<1, STRIDE> {
  static __device__ __forceinline__ void run(uint4* a, const uint4* p, unsigned par) {
    asm volatile(
      "{\n"
      ".reg .pred p, q;\n"
      ".reg .u32 n, t, m;\n"
      "mov.u32 n, 0;\n"
      "V:\n"
      "xor.b32 %3, %3, %6;\n"
      "mov.b32 m, %3;\n"
      "and.b32 m, m, 1;\n"
      "setp.ne.u32 p, m, 0;\n"
      "vote.sync.any.pred p, p, 0xffffffff;\n"
      "@!p bra E;\n"
      "add.u32 n, n, 1;\n"
      "and.b32 t, %3, 1;\n"
      "setp.ne.u32 q, t, 0;\n"
      "xor.b32 %3, %3, %6;\n"
      "@q ld.relaxed.gpu.global.v4.u32 {%0, %1, %2, %3}, [%4+0*%5];\n"
      "setp.lt.u32 p, n, 8192;\n"
      "@p bra V;\n"
      "E:\n"
      "}\n"
      : "+r"(a[0].x), "+r"(a[0].y), "+r"(a[0].z), "+r"(a[0].w)
      : "l"(p), "n"(STRIDE * 16), "r"(par) : "memory");
  }
};

template <int STRIDE> struct Val<3, STRIDE> {
  static __device__ __forceinline__ void run(uint4* a, const uint4* p, unsigned par) {
    asm volatile(
      "{\n"
      ".reg .pred p, q;\n"
      ".reg .u32 n, t, m;\n"
      "mov.u32 n, 0;\n"
      "V:\n"
      "xor.b32 %3, %3, %14;\n"
      "xor.b32 %7, %7, %14;\n"
      "xor.b32 %11, %11, %14;\n"
      "mov.b32 m, %3;\n"
      "or.b32 m, m, %7;\n"
      "or.b32 m, m, %11;\n"
      "and.b32 m, m, 1;\n"
      "setp.ne.u32 p, m, 0;\n"
      "vote.sync.any.pred p, p, 0xffffffff;\n"
      "@!p bra E;\n"
      "add.u32 n, n, 1;\n"
      "and.b32 t, %3, 1;\n"
      "setp.ne.u32 q, t, 0;\n"
      "xor.b32 %3, %3, %14;\n"
      "@q ld.relaxed.gpu.global.v4.u32 {%0, %1, %2, %3}, [%12+0*%13];\n"
      "and.b32 t, %7, 1;\n"
      "setp.ne.u32 q, t, 0;\n"
      "xor.b32 %7, %7, %14;\n"
      "@q ld.relaxed.gpu.global.v4.u32 {%4, %5, %6, %7}, [%12+1*%13];\n"
      "and.b32 t, %11, 1;\n"
      "setp.ne.u32 q, t, 0;\n"
      "xor.b32 %11, %11, %14;\n"
      "@q ld.relaxed.gpu.global.v4.u32 {%8, %9, %10, %11}, [%12+2*%13];\n"
      "setp.lt.u32 p, n, 8192;\n"
      "@p bra V;\n"
      "E:\n"
      "}\n"
      : "+r"(a[0].x), "+r"(a[0].y), "+r"(a[0].z), "+r"(a[0].w), "+r"(a[1].x), "+r"(a[1].y), "+r"(a[1].z), "+r"(a[1].w), "+r"(a[2].x), "+r"(a[2].y), "+r"(a[2].z), "+r"(a[2].w)
      : "l"(p), "n"(STRIDE * 16), "r"(par) : "memory");
  }
};

template <int STRIDE> struct Val<4, STRIDE> {
  static __device__ __forceinline__ void run(uint4* a, const uint4* p, unsigned par) {
    asm volatile(
      "{\n"
      ".reg .pred p, q;\n"
      ".reg .u32 n, t, m;\n"
      "mov.u32 n, 0;\n"
      "V:\n"
      "xor.b32 %3, %3, %18;\n"
      "xor.b32 %7, %7, %18;\n"
      "xor.b32 %11, %11, %18;\n"
      "xor.b32 %15, %15, %18;\n"
      "mov.b32 m, %3;\n"
      "or.b32 m, m, %7;\n"
      "or.b32 m, m, %11;\n"
      "or.b32 m, m, %15;\n"
      "and.b32 m, m, 1;\n"
      "setp.ne.u32 p, m, 0;\n"
      "vote.sync.any.pred p, p, 0xffffffff;\n"
      "@!p bra E;\n"
      "add.u32 n, n, 1;\n"
      "and.b32 t, %3, 1;\n"
      "setp.ne.u32 q, t, 0;\n"
      "xor.b32 %3, %3, %18;\n"
      "@q ld.relaxed.gpu.global.v4.u32 {%0, %1, %2, %3}, [%16+0*%17];\n"
      "and.b32 t, %7, 1;\n"
      "setp.ne.u32 q, t, 0;\n"
      "xor.b32 %7, %7, %18;\n"
      "@q ld.relaxed.gpu.global.v4.u32 {%4, %5, %6, %7}, [%16+1*%17];\n"
      "and.b32 t, %11, 1;\n"
      "setp.ne.u32 q, t, 0;\n"
      "xor.b32 %11, %11, %18;\n"
      "@q ld.relaxed.gpu.global.v4.u32 {%8, %9, %10, %11}, [%16+2*%17];\n"
      "and.b32 t, %15, 1;\n"
      "setp.ne.u32 q, t, 0;\n"
      "xor.b32 %15, %15, %18;\n"
      "@q ld.relaxed.gpu.global.v4.u32 {%12, %13, %14, %15}, [%16+3*%17];\n"
      "setp.lt.u32 p, n, 8192;\n"
      "@p bra V;\n"
      "E:\n"
      "}\n"
      : "+r"(a[0].x), "+r"(a[0].y), "+r"(a[0].z), "+r"(a[0].w), "+r"(a[1].x), "+r"(a[1].y), "+r"(a[1].z), "+r"(a[1].w), "+r"(a[2].x), "+r"(a[2].y), "+r"(a[2].z), "+r"(a[2].w), "+r"(a[3].x), "+r"(a[3].y), "+r"(a[3].z), "+r"(a[3].w)
      : "l"(p), "n"(STRIDE * 16), "r"(par) : "memory");
  }
};

template <int STRIDE> struct Val<8, STRIDE> {
  static __device__ __forceinline__ void run(uint4* a, const uint4* p, unsigned par) {
    asm volatile(
      "{\n"
      ".reg .pred p, q;\n"
      ".reg .u32 n, t, m;\n"
      "mov.u32 n, 0;\n"
      "V:\n"
      "xor.b32 %3, %3, %34;\n"
      "xor.b32 %7, %7, %34;\n"
      "xor.b32 %11, %11, %34;\n"
      "xor.b32 %15, %15, %34;\n"
      "xor.b32 %19, %19, %34;\n"
      "xor.b32 %23, %23, %34;\n"
      "xor.b32 %27, %27, %34;\n"
      "xor.b32 %31, %31, %34;\n"
      "mov.b32 m, %3;\n"
      "or.b32 m, m, %7;\n"
      "or.b32 m, m, %11;\n"
      "or.b32 m, m, %15;\n"
      "or.b32 m, m, %19;\n"
      "or.b32 m, m, %23;\n"
      "or.b32 m, m, %27;\n"
      "or.b32 m, m, %31;\n"
      "and.b32 m, m, 1;\n"
      "setp.ne.u32 p, m, 0;\n"
      "vote.sync.any.pred p, p, 0xffffffff;\n"
      "@!p bra E;\n"
      "add.u32 n, n, 1;\n"
      "and.b32 t, %3, 1;\n"
      "setp.ne.u32 q, t, 0;\n"
      "xor.b32 %3, %3, %34;\n"
      "@q ld.relaxed.gpu.global.v4.u32 {%0, %1, %2, %3}, [%32+0*%33];\n"
      "and.b32 t, %7, 1;\n"
      "setp.ne.u32 q, t, 0;\n"
      "xor.b32 %7, %7, %34;\n"
      "@q ld.relaxed.gpu.global.v4.u32 {%4, %5, %6, %7}, [%32+1*%33];\n"
      "and.b32 t, %11, 1;\n"
      "setp.ne.u32 q, t, 0;\n"
      "xor.b32 %11, %11, %34;\n"
      "@q ld.relaxed.gpu.global.v4.u32 {%8, %9, %10, %11}, [%32+2*%33];\n"
      "and.b32 t, %15, 1;\n"
      "setp.ne.u32 q, t, 0;\n"
      "xor.b32 %15, %15, %34;\n"
      "@q ld.relaxed.gpu.global.v4.u32 {%12, %13, %14, %15}, [%32+3*%33];\n"
      "and.b32 t, %19, 1;\n"
      "setp.ne.u32 q, t, 0;\n"
      "xor.b32 %19, %19, %34;\n"
      "@q ld.relaxed.gpu.global.v4.u32 {%16, %17, %18, %19}, [%32+4*%33];\n"
      "and.b32 t, %23, 1;\n"
      "setp.ne.u32 q, t, 0;\n"
      "xor.b32 %23, %23, %34;\n"
      "@q ld.relaxed.gpu.global.v4.u32 {%20, %21, %22, %23}, [%32+5*%33];\n"
      "and.b32 t, %27, 1;\n"
      "setp.ne.u32 q, t, 0;\n"
      "xor.b32 %27, %27, %34;\n"
      "@q ld.relaxed.gpu.global.v4.u32 {%24, %25, %26, %27}, [%32+6*%33];\n"
      "and.b32 t, %31, 1;\n"
      "setp.ne.u32 q, t, 0;\n"
      "xor.b32 %31, %31, %34;\n"
      "@q ld.relaxed.gpu.global.v4.u32 {%28, %29, %30, %31}, [%32+7*%33];\n"
      "setp.lt.u32 p, n, 8192;\n"
      "@p bra V;\n"
      "E:\n"
      "}\n"
      : "+r"(a[0].x), "+r"(a[0].y), "+r"(a[0].z), "+r"(a[0].w), "+r"(a[1].x), "+r"(a[1].y), "+r"(a[1].z), "+r"(a[1].w), "+r"(a[2].x), "+r"(a[2].y), "+r"(a[2].z), "+r"(a[2].w), "+r"(a[3].x), "+r"(a[3].y), "+r"(a[3].z), "+r"(a[3].w), "+r"(a[4].x), "+r"(a[4].y), "+r"(a[4].z), "+r"(a[4].w), "+r"(a[5].x), "+r"(a[5].y), "+r"(a[5].z), "+r"(a[5].w), "+r"(a[6].x), "+r"(a[6].y), "+r"(a[6].z), "+r"(a[6].w), "+r"(a[7].x), "+r"(a[7].y), "+r"(a[7].z), "+r"(a[7].w)
      : "l"(p), "n"(STRIDE * 16), "r"(par) : "memory");
  }
};

template <int N, int STRIDE> __device__ __forceinline__ void validate(uint4* a, const uint4* p, unsigned tag) { Val<N, STRIDE>::run(a, p, tag & 1); }

__device__ __forceinline__ int fi(float x) { return __float_as_int(x); }

__device__ __forceinline__ void qk_block(float* s, const uint32_t* qf, uint32_t addr) {
  uint32_t kf[4];
  ldsm4(kf, addr);
  mma16816_z(s, qf[0], qf[1], qf[2], qf[3], kf[0], kf[1]);
  mma16816_z(s + 4, qf[0], qf[1], qf[2], qf[3], kf[2], kf[3]);
}
__device__ __forceinline__ void qk_edge(float* s, const uint32_t* qf, uint32_t kaddr, bool p0, bool p1) {
  float d[8];
  qk_block(s, qf, kaddr);
  qk_block(d, qf, kaddr + 16 * 2048);
  s[0] = p0 ? s[0] : d[0];
  s[1] = p1 ? s[1] : d[1];
  s[2] = d[2];
  s[3] = d[3];
  s[6] = p0 ? s[6] : d[6];
  s[7] = p1 ? s[7] : d[7];
}
__device__ __forceinline__ void max_block(int& m0, int& m1, const float* s) {
  m0 = __vimax3_s32(m0, fi(s[0]), fi(s[1])); m1 = __vimax3_s32(m1, fi(s[2]), fi(s[3]));
  m0 = __vimax3_s32(m0, fi(s[4]), fi(s[5])); m1 = __vimax3_s32(m1, fi(s[6]), fi(s[7]));
}
__device__ __forceinline__ void max_finish(int& m0, int& m1, const float (&s)[16][8]) {
  m0 = max(m0, __shfl_xor_sync(0xffffffffu, m0, 1)); m1 = max(m1, __shfl_xor_sync(0xffffffffu, m1, 1));
  m0 = max(m0, __shfl_xor_sync(0xffffffffu, m0, 2)); m1 = max(m1, __shfl_xor_sync(0xffffffffu, m1, 2));
  if (__any_sync(0xffffffffu, (m0 | m1) < 0)) {
    float f0 = -INFINITY, f1 = -INFINITY;
#pragma unroll
    for (int b = 0; b < 16; b++) {
      f0 = fmaxf(fmaxf(f0, s[b][0]), fmaxf(s[b][1], fmaxf(s[b][4], s[b][5])));
      f1 = fmaxf(fmaxf(f1, s[b][2]), fmaxf(s[b][3], fmaxf(s[b][6], s[b][7])));
    }
    f0 = fmaxf(f0, __shfl_xor_sync(0xffffffffu, f0, 1)); f1 = fmaxf(f1, __shfl_xor_sync(0xffffffffu, f1, 1));
    f0 = fmaxf(f0, __shfl_xor_sync(0xffffffffu, f0, 2)); f1 = fmaxf(f1, __shfl_xor_sync(0xffffffffu, f1, 2));
    m0 = fi(f0); m1 = fi(f1);
  }
}
__device__ __forceinline__ uint32_t hadd2(uint32_t a, uint32_t b) { uint32_t r; asm("add.rn.bf16x2 %0, %1, %2;" : "=r"(r) : "r"(a), "r"(b)); return r; }
__device__ __forceinline__ uint32_t packt(float lo, float hi) { return __byte_perm(__float_as_uint(lo), __float_as_uint(hi), 0x7632); }
__device__ __forceinline__ void exp_block(uint32_t* pa, const float* s, float n0, float n1) {
  const float sc = 0.25f * 1.4426950408889634f;
  pa[0] = packt(ex2(fmaf(s[0], sc, n0)), ex2(fmaf(s[1], sc, n0)));
  pa[1] = packt(ex2(fmaf(s[2], sc, n1)), ex2(fmaf(s[3], sc, n1)));
  pa[2] = packt(ex2(fmaf(s[4], sc, n0)), ex2(fmaf(s[5], sc, n0)));
  pa[3] = packt(ex2(fmaf(s[6], sc, n1)), ex2(fmaf(s[7], sc, n1)));
}

__device__ __forceinline__ bool tag_ok(const ulonglong2& a, unsigned tag) { return (unsigned)(a.x >> 32) == tag && (unsigned)(a.y >> 32) == tag; }
__device__ __forceinline__ float lo_f(unsigned long long v) { return __uint_as_float((unsigned)v); }

template <bool V> struct BoolC { static constexpr bool value = V; };

__global__ void __cluster_dims__(2, 1, 1) __launch_bounds__(kThreads, 1)
fused_block_kernel(Scratch* __restrict__ S, const __nv_bfloat16* __restrict__ gx, const __nv_bfloat16* __restrict__ gwmod,
                   const __nv_bfloat16* __restrict__ gc, __nv_bfloat16* __restrict__ gout, const __grid_constant__ Params P) {
  extern __shared__ __align__(1024) uint8_t smem[];
  const uint32_t sb = (uint32_t)__cvta_generic_to_shared(smem);
  const int tid = threadIdx.x, lane = tid & 31;
  const int warp = __shfl_sync(0xffffffffu, tid >> 5, 0);
  const int rank = blockIdx.x & 1;
  int R, g;
  {
    const int t = (int)(blockIdx.x >> 1) - 4;
    if (t < 0) { R = 0; g = 8 + t; }
    else if (t < 32) { R = t & 7; g = t >> 3; }
    else { R = 1 + (t - 32) % 7; g = 4 + (t - 32) / 7; }
  }
  const int r = 2 * R + rank, cta = 8 * r + g;
  const int rd = 2 * R + (g >> 2), gd = 2 * (g & 3) + rank;
  const uint32_t bar = sb + OFF_BAR;

  if (warp >= 8) {
    asm volatile("setmaxnreg.dec.sync.aligned.u32 40;");
    const int aw = warp - 8;
    if (lane == 0) {
      if (aw == 0) {
        asm volatile("prefetch.tensormap [%0];" ::"l"(&P.tm_x) : "memory");
        asm volatile("prefetch.tensormap [%0];" ::"l"(&P.tm_qkv) : "memory");
#pragma unroll
        for (int i = B_X; i < B_WKV + 3; i++) mbar_init(bar + 8 * i, 1);
        fence_async_smem();
      } else if (aw == 1) {
#pragma unroll
        for (int i = B_WKV + 3; i < B_FULL; i++) mbar_init(bar + 8 * i, i == B_XFREE ? 16 : (i >= B_KRDY ? 8 : (i == B_TAB ? 4 : 1)));
        asm volatile("fence.mbarrier_init.release.cluster;" ::: "memory");
        fence_async_smem();
      } else if (aw == 2) {
#pragma unroll
        for (int i = B_FULL; i < B_COUNT; i++) mbar_init(bar + 8 * i, i >= B_EMPTY ? 16 : 1);
        asm volatile("fence.mbarrier_init.release.cluster;" ::: "memory");
        fence_async_smem();
      }
    }
    __syncwarp();
    bar_arrive(1, 384);
    asm volatile("barrier.cluster.arrive.relaxed.aligned;" ::: "memory");
    if (aw == 0 && lane == 0) {
#pragma unroll
      for (int c = 0; c < 8; c++) {
        if (!(c & 1)) mbar_expect(bar + 8 * (B_X + (c >> 1)), 32768);
        tma2d(sb + OFF_WV + c * 2 * U, &P.tm_x, 64 * c, 128 * r, bar + 8 * (B_X + (c >> 1)));
      }
#pragma unroll
      for (int c = 0; c < 3; c++) {
        mbar_expect(bar + 8 * (B_WKV + c), 32768);
        tma2d(sb + kv_off(c), &P.tm_qkv, 512 + 64 * g, 128 * c, bar + 8 * (B_WKV + c));
        tma2d(sb + kv_off(c) + kv_lbo(c), &P.tm_qkv, 1024 + 64 * g, 128 * c, bar + 8 * (B_WKV + c));
      }
    } else if (aw == 3 && lane < 6) {
      asm volatile("prefetch.tensormap [%0];" ::"l"(&P.tm_wo + lane) : "memory");
    }
    FINE(256, 96);
    const unsigned epoch = S->epoch[cta * 32 + lane];
    bar_sync(2, 128);
    const unsigned tag = next_tag(epoch);
    if (aw == 3) S->epoch[cta * 32 + lane] = tag;
    if (aw == 1) {
      if (lane < 2) mbar_expect(bar + 8 * (B_RED + lane), 16384);
      mbar_wait(bar + 8 * B_VN, 0);
      if (lane < 3) l2_prefetch(reinterpret_cast<const uint8_t*>((&P.wg)[lane]) + cta * 11008, 11008);
    } else if (aw == 2) {
      if (lane < 3) mbar_expect(bar + 8 * (B_WKV + 3 + lane), 32768);
      mbar_wait(bar + 8 * B_XFREE, 0);
      if (lane == 0) tma2d_mc(sb + kv_off(3) + rank * kv_lbo(3), &P.tm_qkv, 512 + 512 * rank + 64 * g, 384, bar + 8 * (B_WKV + 3));
      else if (lane < 3) {
        const int i = 2 * (lane - 1) + rank;
        tma2d_mc(sb + OFF_WQ + i * 2 * U, &P.tm_qkv, 64 * g, 128 * i, bar + 8 * (B_WKV + 3 + lane));
      }
      if (lane == 4) l2_prefetch(reinterpret_cast<const uint8_t*>(P.wo) + cta * 4096, 4096);
    } else {
      const int u = (aw == 0 ? 0 : 32) + lane;
      mbar_wait(bar + 8 * B_XFREE, 0);
      const __nv_bfloat16* wp = gwmod + (size_t)(64 * g + (u >> 4)) * 3072 + 1024 + 128 * r + 8 * (u & 15);
      const float sv = silu_bf(__bfloat162float(gc[64 * g + (u >> 4) + 4 * (u & 15)]));
      float acc[8];
#pragma unroll
      for (int i = 0; i < 8; i++) acc[i] = 0.f;
#pragma unroll 1
      for (int bt = 0; bt < 4; bt++) {
        uint4 w[4];
#pragma unroll
        for (int i = 0; i < 4; i++) w[i] = ldg128(wp + (size_t)(bt * 4 + i) * 4 * 3072);
        if (bt == 0) {
#pragma unroll
          for (int i = 4; i < 16; i++) asm volatile("prefetch.global.L1 [%0];" ::"l"(wp + (size_t)i * 4 * 3072));
        }
#pragma unroll
        for (int i = 0; i < 4; i++) {
          const float s = __shfl_sync(0xffffffffu, sv, (lane & 16) + bt * 4 + i);
          const uint32_t* ww = reinterpret_cast<const uint32_t*>(&w[i]);
#pragma unroll
          for (int k = 0; k < 4; k++) {
            acc[2 * k] = fmaf(s, bf_lo(ww[k]), acc[2 * k]);
            acc[2 * k + 1] = fmaf(s, bf_hi(ww[k]), acc[2 * k + 1]);
          }
        }
      }
#pragma unroll
      for (int i = 0; i < 8; i++) acc[i] += __shfl_xor_sync(0xffffffffu, acc[i], 16);
      const int hf = lane >> 4;
      float4 v = hf ? make_float4(acc[4], acc[5], acc[6], acc[7]) : make_float4(acc[0], acc[1], acc[2], acc[3]);
      if (aw == 3) sts128f(sb + OFF_TMP + lane * 16, v.x, v.y, v.z, v.w);
      bar_sync(3, 64);
      if (aw == 0) {
        const uint4 o = lds128(sb + OFF_TMP + lane * 16);
        st_tag(tag, reinterpret_cast<uint4*>(&S->mod2[g][128 * r + 8 * (lane & 15) + 4 * hf]),
               make_uint4((__float_as_uint(v.x + __uint_as_float(o.x))), (__float_as_uint(v.y + __uint_as_float(o.y))),
                          (__float_as_uint(v.z + __uint_as_float(o.z))), (__float_as_uint(v.w + __uint_as_float(o.w)))));
      }
      FINE(352, 106);
    }
    __syncwarp();
    mbar_wait(bar + 8 * B_VN, 0);
    if (aw == 0 && lane == 0) {
      mbar_expect(bar + 8 * B_WO, 65536);
      tma2d(sb + OFF_WV, &P.tm_wo, 64 * gd, 0, bar + 8 * B_WO);
      tma2d(sb + OFF_WV + 4 * U, &P.tm_wo, 64 * gd, 256, bar + 8 * B_WO);
    }
    bar_sync(2, 128);
    {
      const int col = 512 * aw + 64 * gd + 4 * (lane & 15);
      const uint4* mp = reinterpret_cast<const uint4*>(&S->mod2[0][col]);
      float v0 = 0.f, v1 = 0.f, v2 = 0.f, v3 = 0.f;
#pragma unroll 1
      for (int pb = 0; pb < 8; pb += 4) {
        uint4 a[4];
#pragma unroll
        for (int k = 0; k < 4; k++) a[k] = ld_try(mp + (pb + k) * 512);
        validate<4, 512>(a, mp + pb * 512, tag);
#pragma unroll
        for (int k = 0; k < 4; k++) {
          v0 += __uint_as_float(a[k].x); v1 += __uint_as_float(a[k].y); v2 += __uint_as_float(a[k].z); v3 += __uint_as_float(a[k].w);
        }
      }
      const float add = aw == 2 ? 1.f : 0.f;
      sts32(sb + OFF_TMP + 32 * (lane & 15) + 4 * aw, pack2(add + bf_round(v0), add + bf_round(v1)));
      sts32(sb + OFF_TMP + 32 * (lane & 15) + 16 + 4 * aw, pack2(add + bf_round(v2), add + bf_round(v3)));
      __syncwarp();
      if (lane == 0) mbar_arrive(bar + 8 * B_TAB);
      FINE(352, 107);
    }
    asm volatile("barrier.cluster.wait.aligned;" ::: "memory");
    if (aw == 0) {
      const CUtensorMap* tgu = (&P.tm_g0) + (g == 7 ? 1 : 0) + 2 * rank;
      const int sl = g == 7 ? 0 : g;
#pragma unroll 1
      for (int t = 0; t < 18; t++) {
        const int slot = ring_slot(t);
        mbar_wait(bar + 8 * (B_EMPTY + slot), (t / 6) & 1);
        if (t >= INFL) mbar_wait(bar + 8 * (B_FULL + ring_slot(t - INFL)), ((t - INFL) / 6) & 1);
        const uint32_t dst = sb + slot * STAGE, fb = bar + 8 * (B_FULL + slot);
        if (lane == 0) mbar_expect(fb, 32768);
        __syncwarp();
        if (t < 12) {
          if (lane == 0) tma3d_mc(dst + rank * 16384, tgu, 64 * (t >> 2), sl, 128 * (t & 3), fb);
        } else if (lane < 4) {
          const int ch = 2 * (t - 12) + (lane >> 1);
          const int row = 704 * rank + 176 * (ch & 3) + 64 * (ch >> 2);
          tma2d(dst + lane * 8192, &P.tm_wd, 128 * (g & 3) + 64 * (lane & 1), row, fb);
        }
      }
    }
  } else {
    asm volatile("setmaxnreg.inc.sync.aligned.u32 232;");
    const int wg = warp >> 2, gq = lane >> 2, q = lane & 3;
    const uint32_t db = (sb & 0x3FFFF) >> 4;
    uint32_t qf[16];
    unsigned tag;
    {
      const int mrow = 64 * g + (tid >> 3);
      const uint4 wm0 = ldg128(gwmod + (size_t)mrow * 3072 + 64 * r + 8 * (tid & 7));
      const uint4 wm1 = ldg128(gwmod + (size_t)(mrow + 32) * 3072 + 64 * r + 8 * (tid & 7));
      const float c0 = __bfloat162float(gc[mrow]), c1 = __bfloat162float(gc[mrow + 32]);
      const unsigned epoch = S->epoch[(kCtas + cta) * 32 + lane];
      asm volatile("barrier.cluster.arrive.relaxed.aligned;" ::: "memory");
      FINE2(0);
      if (wg == 1) bar_arrive(6, 256);
      {
        const float s0 = silu_bf(c0), s1 = silu_bf(c1);
        float v[8];
        const uint32_t* a = reinterpret_cast<const uint32_t*>(&wm0);
        const uint32_t* b = reinterpret_cast<const uint32_t*>(&wm1);
#pragma unroll
        for (int k = 0; k < 4; k++) {
          v[2 * k] = fmaf(s0, bf_lo(a[k]), s1 * bf_lo(b[k]));
          v[2 * k + 1] = fmaf(s0, bf_hi(a[k]), s1 * bf_hi(b[k]));
        }
        bool up = lane & 16;
#pragma unroll
        for (int i = 0; i < 4; i++) { const float snd = up ? v[i] : v[i + 4], kp = up ? v[i + 4] : v[i]; v[i] = kp + __shfl_xor_sync(0xffffffffu, snd, 16); }
        up = lane & 8;
#pragma unroll
        for (int i = 0; i < 2; i++) { const float snd = up ? v[i] : v[i + 2], kp = up ? v[i + 2] : v[i]; v[i] = kp + __shfl_xor_sync(0xffffffffu, snd, 8); }
        const uint32_t tmp = sb + OFF_TAB;
        const int col = 8 * (lane & 7) + 2 * (lane >> 3);
        sts32(tmp + (warp * 64 + col) * 4, __float_as_uint(v[0]));
        sts32(tmp + (warp * 64 + col + 1) * 4, __float_as_uint(v[1]));
        FINE2(1);
        bar_sync(1, 384);
        tag = next_tag(epoch);
        if (lane < 16) S->st2[gd][16 * (8 * rd + warp) + lane] = make_uint4(0, 0, 0, 0);
        st_tag(tag + 1, &S->o[((8 * r + warp) * 32 + 4 * g + 3) * 32 + lane], make_uint4(0, 0, 0, 0));
        if (tid < 16) {
          float t0 = 0.f, t1 = 0.f, t2 = 0.f, t3 = 0.f;
#pragma unroll
          for (int i = 0; i < 8; i++) {
            const uint4 p = lds128(tmp + i * 256 + tid * 16);
            t0 += __uint_as_float(p.x); t1 += __uint_as_float(p.y); t2 += __uint_as_float(p.z); t3 += __uint_as_float(p.w);
          }
          st_tag(tag, reinterpret_cast<uint4*>(&S->mod1[g][64 * r + 4 * tid]),
                 make_uint4(__float_as_uint(t0), __float_as_uint(t1), __float_as_uint(t2), __float_as_uint(t3)));
        }
        if (warp == 2) S->epoch[(kCtas + cta) * 32 + lane] = tag;
      }
      FINE2(2);
      uint32_t xa[32][4];
      const uint32_t sw = lane & 7, hi = lane >> 4;
      RowNorm n0, n1;
      {
        float ds[4] = {0.f, 0.f, 0.f, 0.f}, g0[4] = {0.f, 0.f, 0.f, 0.f}, g1[4] = {0.f, 0.f, 0.f, 0.f};
        const uint32_t xrow = sb + OFF_WV + (warp * 16 + (lane & 15)) * 128;
        const uint4* mp = reinterpret_cast<const uint4*>(&S->mod1[0][4 * tid]);
        uint4 a[8];
#pragma unroll
        for (int c = 0; c < 4; c++) {
          mbar_wait(bar + 8 * (B_X + c), 0);
          if (c == 2) {
#pragma unroll
            for (int k = 0; k < 8; k++) a[k] = ld_try(mp + k * 256);
          }
#pragma unroll
          for (int k = 8 * c; k < 8 * c + 8; k++) ldsm4(xa[k], xrow + (k >> 2) * 2 * U + (((2 * (k & 3) + hi) ^ sw) << 4));
          if (c == (g >> 1)) {
#pragma unroll
            for (int k = 0; k < 4; k++) {
              uint32_t t[4];
              ldsm4(t, xrow + g * 2 * U + (((2 * k + hi) ^ sw) << 4));
              st_tag(tag, &S->xres[((8 * r + warp) * 32 + 4 * g + k) * 32 + lane], make_uint4(t[0], t[1], t[2], t[3]));
            }
          }
#pragma unroll
          for (int k = 8 * c; k < 8 * c + 8; k++) {
            mma16816(ds, xa[k][0], xa[k][1], xa[k][2], xa[k][3], 0x3F803F80u, 0x3F803F80u);
            mma16816(g0, xa[k][0], xa[k][1], xa[k][2], xa[k][3], xa[k][0], xa[k][2]);
            mma16816(g1, xa[k][0], xa[k][1], xa[k][2], xa[k][3], xa[k][1], xa[k][3]);
          }
          FINE(0, 114 + c);
        }
            validate<8, 256>(a, mp, tag);
        float v0 = 0.f, v1 = 0.f, v2 = 0.f, v3 = 0.f;
#pragma unroll
        for (int k = 0; k < 8; k++) {
          v0 += __uint_as_float(a[k].x); v1 += __uint_as_float(a[k].y); v2 += __uint_as_float(a[k].z); v3 += __uint_as_float(a[k].w);
        }
        const float add = wg ? 1.f : 0.f;
        const int u = tid & 127;
        const uint32_t td = sb + OFF_TAB + (u >> 2) * 64 + (u & 1) * 32 + ((u >> 1) & 1) * 4 + (wg ? 0 : 8);
        sts32(td, pack2(add + bf_round(v0), add + bf_round(v1)));
        sts32(td + 16, pack2(add + bf_round(v2), add + bf_round(v3)));
        const int dl = (lane & 28) | (gq >> 1);
        const float q0 = __shfl_sync(0xffffffffu, (gq & 1) ? g0[1] : g0[0], dl), q1 = __shfl_sync(0xffffffffu, (gq & 1) ? g1[3] : g1[2], dl);
        const float m0 = ds[0] * (1.f / 512.f), m1 = ds[2] * (1.f / 512.f);
        n0 = make_norm(m0, rsqrtf(fmaxf(fmaf(-m0, m0, q0 * (1.f / 512.f)), 0.f) + 1e-5f));
        n1 = make_norm(m1, rsqrtf(fmaxf(fmaf(-m1, m1, q1 * (1.f / 512.f)), 0.f) + 1e-5f));
        FINE2(3);
        FINE2(4);
        asm volatile("barrier.cluster.wait.aligned;" ::: "memory");
        arrive_both(bar + 8 * B_XFREE, lane);
      }
      bar_sync(1, 256);
      FINE2(5);
      const uint32_t trow = sb + (warp * 16 + (lane & 15)) * 128;
      uint4 kvw[8];
      {
        float acc[64];
#pragma unroll
        for (int c = 0; c < 4; c++) {
#pragma unroll
          for (int k = 8 * c; k < 8 * c + 8; k++) {
            const uint4 tb = lds128(sb + OFF_TAB + k * 64 + q * 16);
            xa[k][0] = hfma2(norm1(xa[k][0], n0), tb.x, tb.z); xa[k][1] = hfma2(norm1(xa[k][1], n1), tb.x, tb.z);
            xa[k][2] = hfma2(norm1(xa[k][2], n0), tb.y, tb.w); xa[k][3] = hfma2(norm1(xa[k][3], n1), tb.y, tb.w);
          }
          mbar_wait(bar + 8 * (B_WKV + c), 0);
          bar_sync(6 + wg, 256);
          wg_fence();
#pragma unroll
          for (int k = 0; k < 8; k++)
            wgmma_rs_n128(acc, xa[8 * c + k][0], xa[8 * c + k][1], xa[8 * c + k][2], xa[8 * c + k][3],
                          mkdesc(db + (kv_off(c) >> 4) + ((kv_lbo(c) >> 4) << 16) + k * 128), (c | k) != 0);
          wg_commit();
          wg_wait<1>();
          bar_arrive(7 - wg, 256);
        }
        wg_wait<0>();
        pin(acc);
#pragma unroll
        for (int t = 0; t < 8; t++)
          kvw[t] = make_uint4((pack2(acc[8 * t], acc[8 * t + 1])), (pack2(acc[8 * t + 2], acc[8 * t + 3])),
                              (pack2(acc[8 * t + 4], acc[8 * t + 5])), (pack2(acc[8 * t + 6], acc[8 * t + 7])));
      }
      FINE2(6);
      {
        float acc[32];
        uint4* kdst = &S->kv[cta * 2048 + warp * 128 + lane];
#pragma unroll
        for (int c = 0; c < 4; c++) {
          if (!(c & 1)) mbar_wait(bar + 8 * (B_WKV + 4 + (c >> 1)), 0);
          wg_fence();
#pragma unroll
          for (int k = 8 * c; k < 8 * c + 8; k++) wgmma_rs_n64(acc, xa[k][0], xa[k][1], xa[k][2], xa[k][3], mkdesc(db + (OFF_WQ >> 4) + k * 128), k > 0);
          if (c < 2) {
#pragma unroll
            for (int t = 4 * c; t < 4 * c + 4; t++) {
              st_tag(tag, kdst + c * 1024 + (t & 3) * 32, kvw[t]);
              stsm4(trow + 4 * U + c * OFF_V + (((2 * (t & 3) + hi) ^ sw) << 4), kvw[t].x, kvw[t].y, kvw[t].z, kvw[t].w & ~1u);
            }
          }
        }
        wg_commit();
        __syncwarp();
        if (lane == 0) mbar_arrive(bar + 8 * B_KRDY);
        const int o2 = r >= 2 ? (cta - 16) * 2048 + warp * 128 + lane : g * 2048 + q;
        const int o1 = r >= 1 ? (cta - 8) * 2048 + warp * 128 + lane : g * 2048 + q;
        const uint4* s2 = &S->kv[o2];
        const uint4* s1 = &S->kv[o1];
        uint4 f[4][4];
#pragma unroll
        for (int t = 0; t < 4; t++) { f[0][t] = ld_try(s2 + 32 * t); f[1][t] = ld_try(s1 + 32 * t); }
        wg_wait<0>();
        pin(acc);
#pragma unroll
        for (int t = 0; t < 4; t++) { f[2][t] = ld_try(s2 + 1024 + 32 * t); f[3][t] = ld_try(s1 + 1024 + 32 * t); }
#pragma unroll
        for (int i = 0; i < 16; i++) qf[i] = pack2(acc[2 * i], acc[2 * i + 1]);
        arrive_both(bar + 8 * (B_EMPTY + 5 + (lane >> 1)), lane < 4 ? (lane & 1) : 2);
        FINE2(8);
        mbar_wait(bar + 8 * B_KRDY, 0);
#pragma unroll
        for (int i = 0; i < 4; i++) {
          validate<4, 32>(f[i], ((i & 1) ? s1 : s2) + (i >> 1) * 1024, tag);
          if (r + (i & 1) < 2) {
#pragma unroll
            for (int t = 0; t < 4; t++) f[i][t] = i < 2 ? make_uint4(f[i][t].x, f[i][t].x, f[i][t].z, f[i][t].z) : make_uint4(0, 0, 0, 0);
          }
#pragma unroll
          for (int t = 0; t < 4; t++)
            stsm4(trow + (i & 1) * 2 * U + (i >> 1) * OFF_V + (((2 * t + hi) ^ sw) << 4), f[i][t].x, f[i][t].y, f[i][t].z, f[i][t].w);
          if (i & 1) {
            __syncwarp();
            if (lane == 0) mbar_arrive(bar + 8 * (B_KN + (i >> 1)));
          }
          if (i == 1) FINE2(7);
        }
      }
    }
    const int rt = 8 * rd + warp, fo = (rt * 32 + 4 * gd) * 32 + lane;
    const uint4* osrc = &S->o[rt * 32 * 32 + lane];
    uint4 oa[32], xr[4];
    {
      mbar_wait(bar + 8 * B_KN, 0);
      FINE2(9);
      const int b0 = r >= 2 ? 0 : 16 - 8 * r - warp;
      const bool p0 = 2 * q > gq, p1 = 2 * q + 1 > gq;
      const uint32_t msk = (p0 ? 0xFFFFu : 0u) | (p1 ? 0xFFFF0000u : 0u);
      const uint32_t lm = b0 > 0 ? ~msk : ~0u, lo = b0 > 0 ? 0u : ~0u;
      const uint32_t krow = sb + OFF_K + warp * 2048 + ((lane >> 4) * 8 + (lane & 7)) * 128;
      const uint32_t vrow = sb + OFF_V + warp * 2048 + (lane & 15) * 128;
      uint4* dst = &S->o[((8 * r + warp) * 32 + 4 * g) * 32 + lane];
      const uint32_t kc = (lane >> 3) & 1, vc = lane >> 4, sw = lane & 7;
      const int zero = b0 >> 8;
      float s[16][8];
      int m0 = 0x80000000, m1 = 0x80000000;
      {
        const uint32_t ka = krow + ((kc ^ sw) << 4);
#pragma unroll
        for (int b = 15; b > 0; b--) qk_block(s[b], qf, ka + b * 2048);
        qk_edge(s[0], qf, ka, p0, p1);
        int m2 = m0, m3 = m0;
#pragma unroll
        for (int b = 15; b >= 0; b--) { if (b & 1) max_block(m0, m1, s[b]); else max_block(m2, m3, s[b]); }
        m0 = max(m0, m2); m1 = max(m1, m3);
      }
      mbar_wait(bar + 8 * B_VN, 0);
#pragma unroll
      for (int k = 0; k < 4; k++) st_tag(tag + 1, &S->h2[fo + 32 * k], make_uint4(0, 0, 0, 0));
      FINE2(23);
#define ON(b) ((b) >= b0 ? ones : 0u)
      auto head = [&](int h, auto last_c) {
        constexpr bool LAST = decltype(last_c)::value;
        max_finish(m0, m1, s);
        const float sc = 0.25f * 1.4426950408889634f;
        const float n0 = -__int_as_float(m0) * sc, n1 = -__int_as_float(m1) * sc;
        m0 = m1 = 0x80000000;
        const uint32_t ka = krow + (((2 * (h + 1) + kc) ^ sw) << 4);
        const uint32_t va = vrow + (((2 * h + vc) ^ sw) << 4);
        const uint32_t ones = 0x3F803F80u;
        float o0[4], o1[4], l[4], a0 = n0, a1 = n1;
        uint32_t pa[4], vf[4], h0, h1;
#pragma unroll
        for (int b = 15; b >= 0; b--) {
          if (!LAST && (b & 3) == 3) { a0 = __int_as_float(fi(n0) ^ (m0 & zero)); a1 = __int_as_float(fi(n1) ^ (m1 & zero)); }
          exp_block(pa, s[b], a0, a1);
          if (b == 0) mma16816(l, h0, h1, hadd2(pa[0] & lm, pa[2] & lo), hadd2(pa[1], pa[3] & lm), ON(1), ones);
          else if (b & 1) { h0 = hadd2(pa[0], pa[2]); h1 = hadd2(pa[1], pa[3]); }
          else if (b == 14) mma16816_z(l, h0, h1, hadd2(pa[0], pa[2]), hadd2(pa[1], pa[3]), ON(b + 1), ON(b));
          else mma16816(l, h0, h1, hadd2(pa[0], pa[2]), hadd2(pa[1], pa[3]), ON(b + 1), ON(b));
          ldsm4t(vf, va + b * 2048);
          if (b == 15) {
            mma16816_z(o0, pa[0], pa[1], pa[2], pa[3], vf[0], vf[1]);
            mma16816_z(o1, pa[0], pa[1], pa[2], pa[3], vf[2], vf[3]);
          } else if (b > 0) {
            mma16816(o0, pa[0], pa[1], pa[2], pa[3], vf[0], vf[1]);
            mma16816(o1, pa[0], pa[1], pa[2], pa[3], vf[2], vf[3]);
          } else {
            mma16816(o0, pa[0] & msk, 0u, pa[2], pa[3] & msk, vf[0], vf[1]);
            mma16816(o1, pa[0] & msk, 0u, pa[2], pa[3] & msk, vf[2], vf[3]);
            ldsm4t(vf, va + 16 * 2048);
            mma16816(o0, pa[0] & ~msk, pa[1], 0u, pa[3] & ~msk, vf[0], vf[1]);
            mma16816(o1, pa[0] & ~msk, pa[1], 0u, pa[3] & ~msk, vf[2], vf[3]);
          }
          if (!LAST) {
            if (b > 0) qk_block(s[b], qf + 4, ka + b * 2048);
            else qk_edge(s[0], qf + 4, ka, p0, p1);
            if (b < 15) max_block(m0, m1, s[b + 1]);
          } else if ((b & 1) == 0 && b > 0) {
            const int i0 = 24 - 2 * b;
#pragma unroll
            for (int k = 0; k < 4; k++) {
              if (b == 14) xr[k] = ld_try(&S->xres[fo + 32 * k]);
              else oa[i0 + k] = ld_try(osrc + (4 * ((i0 + k) & 7) + ((i0 + k) >> 3)) * 32);
            }
            mbar_wait(bar + 8 * (b == 2 ? B_TAB : B_WO), 0);
          }
        }
        if (!LAST) max_block(m0, m1, s[0]);
        const float i0 = __fdividef(1.f, l[0]), i1 = __fdividef(1.f, l[2]);
        st_tag(tag, dst + 32 * h, make_uint4((pack2(o0[0] * i0, o0[1] * i0)), (pack2(o0[2] * i1, o0[3] * i1)),
                                        (pack2(o1[0] * i0, o1[1] * i0)), (pack2(o1[2] * i1, o1[3] * i1))));
        FINE2(10 + h);
      };
#pragma unroll 1
      for (int h = 0; h < 3; h++) {
        head(h, BoolC<false>());
#pragma unroll
        for (int i = 4; i < 12; i++) qf[i] = qf[i + 4];
      }
      head(3, BoolC<true>());
    }
    {
      float acc[32];
#pragma unroll
      for (int h = 0; h < 4; h++) {
        validate<8, 128>(&oa[8 * h], osrc + 32 * h, tag);
        if (h == REL_H) {
          fence_async_smem();
          __syncwarp();
          arrive_both(bar + 8 * (B_EMPTY + (lane >> 1)), lane < 6 ? (lane & 1) : 2);
        }
        FINE2(14 + h);
        wg_fence();
#pragma unroll
        for (int s = 0; s < 8; s++)
          wgmma_rs_n64(acc, oa[8 * h + s].x, oa[8 * h + s].y, oa[8 * h + s].z, oa[8 * h + s].w, mkdesc(db + (OFF_WV >> 4) + (4 * s + h) * 128), (h | s) != 0);
        if (h == O3_H) {
#pragma unroll
          for (int i = 24; i < 32; i++) oa[i] = ld_try(osrc + (4 * (i & 7) + 3) * 32);
          validate<4, 32>(xr, &S->xres[fo], tag);
        }
      }
      wg_commit();
      wg_wait<0>();
      pin(acc);
      FINE2(18);
      float s0 = 0.f, s1 = 0.f;
      uint32_t tsc[8], tsh[8];
#pragma unroll
      for (int t = 0; t < 8; t++) {
        const uint4 tb = lds128(sb + OFF_TMP + (4 * t + q) * 16);
        tsh[t] = tb.y; tsc[t] = tb.z;
        const float gl = bf_lo(tb.x), gh = bf_hi(tb.x);
        const uint32_t xa = (t & 1) ? xr[t >> 1].z : xr[t >> 1].x, xb = (t & 1) ? xr[t >> 1].w : xr[t >> 1].y;
        acc[4 * t] = fmaf(gl, acc[4 * t], bf_lo(xa));
        acc[4 * t + 1] = fmaf(gh, acc[4 * t + 1], bf_hi(xa));
        acc[4 * t + 2] = fmaf(gl, acc[4 * t + 2], bf_lo(xb));
        acc[4 * t + 3] = fmaf(gh, acc[4 * t + 3], bf_hi(xb));
        s0 += acc[4 * t] + acc[4 * t + 1];
        s1 += acc[4 * t + 2] + acc[4 * t + 3];
      }
      s0 += __shfl_xor_sync(0xffffffffu, s0, 1); s1 += __shfl_xor_sync(0xffffffffu, s1, 1);
      s0 += __shfl_xor_sync(0xffffffffu, s0, 2); s1 += __shfl_xor_sync(0xffffffffu, s1, 2);
      s0 *= (1.f / 64.f); s1 *= (1.f / 64.f);
      float q0 = 0.f, q1 = 0.f;
#pragma unroll
      for (int t = 0; t < 8; t++) {
        float d;
        d = acc[4 * t] - s0; q0 = fmaf(d, d, q0);
        d = acc[4 * t + 1] - s0; q0 = fmaf(d, d, q0);
        d = acc[4 * t + 2] - s1; q1 = fmaf(d, d, q1);
        d = acc[4 * t + 3] - s1; q1 = fmaf(d, d, q1);
      }
      q0 += __shfl_xor_sync(0xffffffffu, q0, 1); q1 += __shfl_xor_sync(0xffffffffu, q1, 1);
      q0 += __shfl_xor_sync(0xffffffffu, q0, 2); q1 += __shfl_xor_sync(0xffffffffu, q1, 2);
      if (q < 2) {
        const unsigned long long tg = (unsigned long long)tag << 32;
        st_rlx2(&S->st2[gd][16 * rt + gq + 8 * q], tg | __float_as_uint(q == 0 ? s0 : s1), tg | __float_as_uint(q == 0 ? q0 : q1));
      }
      uint32_t xw[16];
#pragma unroll
      for (int i = 0; i < 16; i++) xw[i] = pack2(acc[2 * i], acc[2 * i + 1]);
      FINE2(20);
      const uint4* sp = &S->st2[2 * q][16 * rt + gq];
      ulonglong2 ua, ub, uc, ud;
      int n = 0;
      do {
        ua = ld_rlx2(sp); ub = ld_rlx2(sp + 2048); uc = ld_rlx2(sp + 8); ud = ld_rlx2(sp + 2048 + 8);
      } while (__any_sync(0xffffffffu, !(tag_ok(ua, tag) && tag_ok(ub, tag) && tag_ok(uc, tag) && tag_ok(ud, tag))) && ++n < kSpinLimit);
      FINE2(21);
      const float ma = lo_f(ua.x), mb = lo_f(ub.x), mc = lo_f(uc.x), md = lo_f(ud.x);
      float m0 = ma + mb, m1 = mc + md;
      m0 += __shfl_xor_sync(0xffffffffu, m0, 1); m1 += __shfl_xor_sync(0xffffffffu, m1, 1);
      m0 += __shfl_xor_sync(0xffffffffu, m0, 2); m1 += __shfl_xor_sync(0xffffffffu, m1, 2);
      m0 *= 0.125f; m1 *= 0.125f;
      float v0 = 64.f * ((ma - m0) * (ma - m0) + (mb - m0) * (mb - m0)) + lo_f(ua.y) + lo_f(ub.y);
      float v1 = 64.f * ((mc - m1) * (mc - m1) + (md - m1) * (md - m1)) + lo_f(uc.y) + lo_f(ud.y);
      v0 += __shfl_xor_sync(0xffffffffu, v0, 1); v1 += __shfl_xor_sync(0xffffffffu, v1, 1);
      v0 += __shfl_xor_sync(0xffffffffu, v0, 2); v1 += __shfl_xor_sync(0xffffffffu, v1, 2);
      const float r0 = rsqrtf(v0 * (1.f / 512.f) + 1e-5f), r1 = rsqrtf(v1 * (1.f / 512.f) + 1e-5f);
      const float c0 = -m0 * r0, c1 = -m1 * r1;
      uint32_t hw[16];
#pragma unroll
      for (int i = 0; i < 16; i++) {
        const float rs = (i & 1) ? r1 : r0, cs = (i & 1) ? c1 : c0;
        hw[i] = (hfma2(pack2(fmaf(bf_lo(xw[i]), rs, cs), fmaf(bf_hi(xw[i]), rs, cs)), tsc[i >> 1], tsh[i >> 1]));
      }
#pragma unroll
      for (int k = 0; k < 4; k++) st_tag(tag, &S->h2[fo + 32 * k], make_uint4(hw[4 * k], hw[4 * k + 1], hw[4 * k + 2], hw[4 * k + 3]));
      mbar_wait(bar + 8 * (B_EMPTY + 2), 0);
#pragma unroll
      for (int k = 0; k < 4; k++)
        asm volatile("st.shared.v4.u32 [%0], {%1,%2,%3,%4};" ::"r"(sb + OFF_RED + k * 4096 + tid * 16), "r"(xw[4 * k]), "r"(xw[4 * k + 1]), "r"(xw[4 * k + 2]), "r"(xw[4 * k + 3]) : "memory");
      FINE2(22);
    }
    const uint4* hsrc = &S->hh[(rt * 86 + 44 * rank) * 32 + lane];
    uint4 a[3][8];
    {
      const int rg = 8 * r + warp;
      const uint4* src = &S->h2[rg * 32 * 32 + lane];
      uint4 xa[32];
      {
        const unsigned t0 = clock32();
        while (clock32() - t0 < H2_WAIT) {}
#pragma unroll
        for (int k = 0; k < 16; k++) xa[k] = ld_try(src + 32 * k);
      }
      arrive_both(bar + 8 * (B_EMPTY + 3 + (lane >> 1)), lane < 4 ? (lane & 1) : 2);
      FINE2(47);
      const uint32_t dg = db + ((16384 >> 4) << 16);
      uint4* dst = &S->hh[(rg * 86 + 11 * g) * 32 + lane];
#define HH_OUT(ACC, K, OFFS)                                                                                          \
  st_tag(tag, dst + (OFFS) + 32 * (K),                                                                                     \
         make_uint4((pack2(ACC[8 * (K)] * ACC[32 + 8 * (K)], ACC[8 * (K) + 1] * ACC[33 + 8 * (K)])),                \
                    (pack2(ACC[8 * (K) + 2] * ACC[34 + 8 * (K)], ACC[8 * (K) + 3] * ACC[35 + 8 * (K)])),            \
                    (pack2(ACC[8 * (K) + 4] * ACC[36 + 8 * (K)], ACC[8 * (K) + 5] * ACC[37 + 8 * (K)])),            \
                    (pack2(ACC[8 * (K) + 6] * ACC[38 + 8 * (K)], ACC[8 * (K) + 7] * ACC[39 + 8 * (K)]))))
#define GU_TURN(ACC, FN, C, T)                                                                                        \
  {                                                                                                                   \
    const int slot = ring_slot(T);                                                                                    \
    const uint32_t d = dg + slot * (STAGE >> 4);                                                                      \
    mbar_wait(bar + 8 * (B_FULL + slot), (T) >= 6);                                                                   \
    bar_sync(6 + wg, 256);                                                                                            \
    wg_fence();                                                                                                       \
    _Pragma("unroll") for (int k = 0; k < 8; k++)                                                                     \
      FN(ACC, xa[8 * (C) + k].x, xa[8 * (C) + k].y, xa[8 * (C) + k].z, xa[8 * (C) + k].w, mkdesc(d + k * 128), ((C) | k) != 0); \
    wg_commit();                                                                                                      \
    bar_arrive(7 - wg, 256);                                                                                          \
    if ((C) > 0) {                                                                                                    \
      wg_wait<1>();                                                                                                   \
      arrive_both(bar + 8 * (B_EMPTY + ring_slot((T) - 1)), lane);                                                    \
    }                                                                                                                 \
  }
#define GU_END(ACC, T)                                                                                                \
  {                                                                                                                   \
    wg_wait<0>();                                                                                                     \
    pin(ACC);                                                                                                         \
    arrive_both(bar + 8 * (B_EMPTY + ring_slot(T)), lane);                                                            \
  }
#pragma unroll 1
      for (int p = 0; p < 2; p++) {
        float acc[64];
#pragma unroll
        for (int c = 0; c < 4; c++) {
          if (p == 0) validate<8, 32>(&xa[8 * c], src + 256 * c, tag);
          GU_TURN(acc, wgmma_rs_n128, c, 4 * p + c);
          if (p == 0 && c < 2) {
#pragma unroll
            for (int k = 16 + 8 * c; k < 24 + 8 * c; k++) xa[k] = ld_try(src + 32 * k);
          }
          FINE2(24 + 4 * p + c);
        }
        GU_END(acc, 4 * p + 3);
#pragma unroll
        for (int k = 0; k < 4; k++) HH_OUT(acc, k, 128 * p);
      }
      {
        float acc[56];
#pragma unroll
        for (int c = 0; c < 4; c++) {
          GU_TURN(acc, wgmma_rs_n112, c, 8 + c);
          if (c > 0) {
#pragma unroll
            for (int e = 0; e < 8; e++) a[c - 1][e] = ld_try(hsrc + dn_step(c - 1, e) * 32);
          }
          FINE2(32 + c);
        }
        GU_END(acc, 11);
#pragma unroll
        for (int k = 0; k < 3; k++)
          if (k == 0 || g != 7) HH_OUT(acc, k, 256);
      }
    }
    FINE2(36);
    {
      const uint4* src = hsrc;
      float acc[64];
      const uint32_t dd = db + ((8192 >> 4) << 16);
#pragma unroll
      for (int t = 0; t < 6; t++) {
        uint4* at = a[t % 3];
        if (t < 4) {
          validate<4, 32>(at, src + dn_step(t, 0) * 32, tag);
          validate<4, 32>(at + 4, src + dn_step(t, 4) * 32, tag);
        } else {
          validate<3, 32>(at, src + (22 * (t - 4) + 8) * 32, tag);
          if (t == 4 || rank == 0) validate<3, 32>(at + 4, src + (22 * (t - 4) + 19) * 32, tag);
          else validate<1, 32>(at + 4, src + 41 * 32, tag);
        }
        const uint32_t d = dd + ring_slot(t) * (STAGE >> 4);
        mbar_wait(bar + 8 * (B_FULL + ring_slot(t)), 0);
        bar_sync(6 + wg, 256);
        wg_fence();
#pragma unroll
        for (int e = 0; e < 8; e++)
          if (t < 4 || ((e & 3) != 3 && (t == 4 || e < 5)))
            wgmma_rs_n128(acc, at[e].x, at[e].y, at[e].z, at[e].w, mkdesc(d + (e >> 2) * 1024 + (e & 3) * 128), (t | e) != 0);
        if (t == 5 && rank == 0) {
          wg_fence();
#pragma unroll
          for (int e = 5; e < 7; e++) wgmma_rs_n128(acc, at[e].x, at[e].y, at[e].z, at[e].w, mkdesc(d + (e >> 2) * 1024 + (e & 3) * 128), true);
        }
        wg_commit();
        bar_arrive(7 - wg, 256);
        wg_wait<1>();
        uint4* an = a[(t + 2) % 3];
        if (t == 1) {
#pragma unroll
          for (int e = 0; e < 8; e++) an[e] = ld_try(src + dn_step(3, e) * 32);
        } else if (t == 2 || t == 3) {
#pragma unroll
          for (int e = 0; e < 3; e++) {
            an[e] = ld_try(src + (22 * (t - 2) + 8 + e) * 32);
            if (t == 2 || e == 0 || rank == 0) an[4 + e] = ld_try(src + (22 * (t - 2) + 19 + e) * 32);
          }
        } else if (t == 4) {
#pragma unroll
          for (int e = 0; e < 4; e++) an[e] = lds128(sb + OFF_RED + e * 4096 + tid * 16);
          arrive_both(bar + 8 * (B_EMPTY + 2), lane + (int)((an[0].x ^ an[1].x ^ an[2].x ^ an[3].x) == 0x12345u && tag == 0) * 32);
        }
        FINE2(37 + t);
      }
      mbar_wait(bar + 8 * (B_EMPTY + 2), 1);
      wg_wait<0>();
      pin(acc);
      FINE2(43);
      uint32_t rbar;
      asm volatile("mapa.shared::cluster.u32 %0, %1, %2;" : "=r"(rbar) : "r"(bar), "r"(rank ^ 1));
      const uint32_t roff = OFF_RED + warp * 4096 + lane * 16;
      const uint32_t rbuf = rbar - OFF_BAR + roff, rb = rbar + 8 * (B_RED + wg);
      if (rank == 0) {
#pragma unroll
        for (int i = 0; i < 8; i++)
          asm volatile("st.async.weak.shared::cluster.mbarrier::complete_tx::bytes.v4.f32 [%0], {%1,%2,%3,%4}, [%5];" ::"r"(rbuf + i * 512),
                       "f"(acc[32 + 4 * i]), "f"(acc[33 + 4 * i]), "f"(acc[34 + 4 * i]), "f"(acc[35 + 4 * i]), "r"(rb) : "memory");
      } else {
#pragma unroll
        for (int i = 0; i < 8; i++)
          asm volatile("st.async.weak.shared::cluster.mbarrier::complete_tx::bytes.v4.f32 [%0], {%1,%2,%3,%4}, [%5];" ::"r"(rbuf + i * 512),
                       "f"(acc[4 * i]), "f"(acc[4 * i + 1]), "f"(acc[4 * i + 2]), "f"(acc[4 * i + 3]), "r"(rb) : "memory");
#pragma unroll
        for (int i = 0; i < 32; i++) acc[i] = acc[32 + i];
      }
      FINE2(44);
      mbar_wait_cluster(bar + 8 * (B_RED + wg), 0);
      FINE2(45);
      uint32_t ow[16];
#pragma unroll
      for (int t = 0; t < 8; t++) {
        const uint4 o = lds128(sb + roff + t * 512);
        const uint32_t gb = lds32(sb + OFF_TMP + (4 * t + q) * 16 + 12);
        const float gl = bf_lo(gb), gh = bf_hi(gb);
        const uint32_t xa = (t & 1) ? a[0][t >> 1].z : a[0][t >> 1].x, xb = (t & 1) ? a[0][t >> 1].w : a[0][t >> 1].y;
        ow[2 * t] = pack2(fmaf(gl, acc[4 * t] + __uint_as_float(o.x), bf_lo(xa)), fmaf(gh, acc[4 * t + 1] + __uint_as_float(o.y), bf_hi(xa)));
        ow[2 * t + 1] = pack2(fmaf(gl, acc[4 * t + 2] + __uint_as_float(o.z), bf_lo(xb)), fmaf(gh, acc[4 * t + 3] + __uint_as_float(o.w), bf_hi(xb)));
      }
      const uint32_t patch = sb + OFF_RED + warp * 4096;
      __syncwarp();
#pragma unroll
      for (int t = 0; t < 4; t++)
        stsm4(patch + (lane & 15) * 128 + (((2 * t + (lane >> 4)) ^ (lane & 7)) << 4), ow[4 * t], ow[4 * t + 1], ow[4 * t + 2], ow[4 * t + 3]);
      __syncwarp();
      __nv_bfloat16* op = gout + (size_t)(16 * rt + (lane >> 3)) * kD + 64 * gd + (lane & 7) * 8;
#pragma unroll
      for (int t = 0; t < 4; t++) {
        const int row = 4 * t + (lane >> 3);
        asm volatile("" ::: "memory");
        *reinterpret_cast<uint4*>(op + 4 * t * kD) = lds128(patch + row * 128 + (((lane & 7) ^ (row & 7)) << 4));
      }
      FINE2(46);
    }
  }
}

typedef CUresult (*EncodeFn)(CUtensorMap*, CUtensorMapDataType, cuuint32_t, void*, const cuuint64_t*, const cuuint64_t*, const cuuint32_t*,
                             const cuuint32_t*, CUtensorMapInterleave, CUtensorMapSwizzle, CUtensorMapL2promotion, CUtensorMapFloatOOBfill);

void encode(EncodeFn fn, CUtensorMap* tm, const void* base, int rank, const cuuint64_t* dims, const cuuint64_t* strides, const cuuint32_t* box) {
  const cuuint32_t es[5] = {1, 1, 1, 1, 1};
  CUresult rc = fn(tm, CU_TENSOR_MAP_DATA_TYPE_BFLOAT16, rank, const_cast<void*>(base), dims, strides, box, es, CU_TENSOR_MAP_INTERLEAVE_NONE,
                   CU_TENSOR_MAP_SWIZZLE_128B, CU_TENSOR_MAP_L2_PROMOTION_L2_128B, CU_TENSOR_MAP_FLOAT_OOB_FILL_NONE);
  (void)rc;
}

}

extern "C" void kernel_launch(void* const* d_in, const int* in_sizes, int n_in, void* d_out, int out_size) {
  (void)in_sizes; (void)n_in; (void)out_size;
  static EncodeFn fn = nullptr;
  static Scratch* scratch = nullptr;
  if (!fn) {
    void* p = nullptr;
    cudaDriverEntryPointQueryResult qr;
    cudaGetDriverEntryPoint("cuTensorMapEncodeTiled", &p, cudaEnableDefault, &qr);
    fn = (EncodeFn)p;
    cudaGetSymbolAddress((void**)&scratch, g_s);
    cudaFuncSetAttribute(fused_block_kernel, cudaFuncAttributeMaxDynamicSharedMemorySize, SMEM_BYTES);
  }
  Params P;
  const __nv_bfloat16* x = (const __nv_bfloat16*)d_in[0];
  const __nv_bfloat16* wqkv = (const __nv_bfloat16*)d_in[1];
  P.wo = (const __nv_bfloat16*)d_in[2];
  P.wg = (const __nv_bfloat16*)d_in[4];
  P.wu = (const __nv_bfloat16*)d_in[5];
  P.wd = (const __nv_bfloat16*)d_in[6];
  {
    const cuuint64_t dims[2] = {1536, 512};
    const cuuint64_t str[1] = {3072};
    const cuuint32_t box[2] = {64, 128};
    encode(fn, &P.tm_qkv, wqkv, 2, dims, str, box);
    const cuuint64_t dimx[2] = {512, 2048};
    const cuuint64_t strx[1] = {1024};
    encode(fn, &P.tm_x, x, 2, dimx, strx, box);
  }
  {
    const cuuint64_t dims[2] = {512, 512};
    const cuuint64_t str[1] = {1024};
    const cuuint32_t box[2] = {64, 256};
    encode(fn, &P.tm_wo, P.wo, 2, dims, str, box);
  }
  {
    const cuuint64_t dims0[3] = {176, 7, 512}, dims1[3] = {144, 1, 512};
    const cuuint64_t str[2] = {352, 2 * kF};
    const cuuint32_t box[3] = {64, 1, 128};
    encode(fn, &P.tm_g0, P.wg, 3, dims0, str, box);
    encode(fn, &P.tm_u0, P.wu, 3, dims0, str, box);
    encode(fn, &P.tm_g1, P.wg + 7 * 176, 3, dims1, str, box);
    encode(fn, &P.tm_u1, P.wu + 7 * 176, 3, dims1, str, box);
  }
  {
    const cuuint64_t dims[2] = {512, kF};
    const cuuint64_t str[1] = {1024};
    const cuuint32_t box[2] = {64, 64};
    encode(fn, &P.tm_wd, P.wd, 2, dims, str, box);
  }
  fused_block_kernel<<<kCtas, kThreads, SMEM_BYTES>>>(scratch, x, (const __nv_bfloat16*)d_in[8], (const __nv_bfloat16*)d_in[7], (__nv_bfloat16*)d_out, P);
}
```

```cpp
#include <cuda_runtime.h>
#include <cuda_bf16.h>
#include <cuda.h>
#include <stdint.h>

#define NORM3 0
#define REL_H 3
#define O3_H 2
#define H2_WAIT 200
#define XPRE 0
#define KVINV 0
#define HHINV 0
#define LAG 0
#define TURNS 1
#define WD_PACE 250
#define PF_STEP 3
#define ST_WAIT 0
#define PF_B0 11
#define PF_B1 6
#define PF_B2 2
#define KF_C 2
#define VF_C 3
#define INFL 2
namespace {

constexpr int kD = 512, kF = 1376;
constexpr float kScale = 0.25f * 1.4426950408889634f;
constexpr int kThreads = 384;
constexpr int kCtas = 128;

constexpr uint32_t U = 8192;
constexpr uint32_t OFF_K = 0;
constexpr uint32_t OFF_V = 6 * U;
constexpr uint32_t OFF_WV = 12 * U;
constexpr uint32_t OFF_WQ = 20 * U;
constexpr uint32_t STAGE = 4 * U;
constexpr uint32_t OFF_RED = 2 * STAGE;
constexpr uint32_t OFF_MISC = 28 * U;
constexpr uint32_t OFF_BAR = OFF_MISC;
constexpr uint32_t OFF_TMP = OFF_MISC + 512;
constexpr uint32_t OFF_TAB = OFF_MISC + 1024;
constexpr uint32_t SMEM_BYTES = OFF_MISC + 3072;

enum {
  B_X = 0  , B_WKV = 2  ,
  B_WO = 8, B_XR = 9, B_RED = 10  ,
  B_TAB = 12,
  B_KRDY = 13, B_KN = 14, B_VN = 15,
  B_XFREE = 16,
  B_FULL = 17  ,
  B_EMPTY = 24  ,
  B_COUNT = 31
};
__host__ __device__ constexpr uint32_t kv_off(int c) { return c == 0 ? 4 * U : (c == 1 ? 0 : (c == 2 ? 6 * U : OFF_WV)); }
__host__ __device__ constexpr uint32_t kv_lbo(int c) { return c == 0 ? 6 * U : 2 * U; }

__host__ __device__ constexpr int ring_slot(int t) { return (0x431065 >> (4 * (t % 6))) & 7; }
__host__ __device__ constexpr int dn_step(int t, int e) { return 11 * (2 * (t & 1) + (e >> 2)) + 4 * (t >> 1) + (e & 3); }

struct Scratch {
  uint4 o[128 * 32 * 32];
  uint4 h2[128 * 32 * 32];
  uint4 hh[128 * 86 * 32];
  uint4 kv[kCtas * 2 * 1024];
  float mod1[8][1024];
  float mod2[8][2048];
  uint4 st2[8][2048];
  unsigned epoch[2 * kCtas * 32];
};
__device__ Scratch g_s;
#define FINE(t, i) do {} while (0)
#define FINE2(i) do {} while (0)

struct Params {
  CUtensorMap tm_x, tm_qkv, tm_wo, tm_g0, tm_g1, tm_u0, tm_u1, tm_wd;
  const __nv_bfloat16 *wo, *wg, *wu, *wd;
};

constexpr int kSpinLimit = 1 << 13;

__device__ __forceinline__ void mbar_init(uint32_t b, int cnt) { asm volatile("mbarrier.init.shared::cta.b64 [%0], %1;" ::"r"(b), "r"(cnt) : "memory"); }
__device__ __forceinline__ void mbar_expect(uint32_t b, uint32_t bytes) { asm volatile("mbarrier.arrive.expect_tx.shared::cta.b64 _, [%0], %1;" ::"r"(b), "r"(bytes) : "memory"); }
__device__ __forceinline__ void mbar_arrive(uint32_t b) { asm volatile("mbarrier.arrive.shared::cta.b64 _, [%0];" ::"r"(b) : "memory"); }
__device__ __forceinline__ void mbar_wait(uint32_t b, uint32_t ph) {
  asm volatile("{\n.reg .pred p;\n.reg .u32 n;\nmov.u32 n, 0;\n"
               "W: mbarrier.try_wait.parity.shared::cta.b64 p, [%0], %1;\n@p bra D;\n"
               "add.u32 n, n, 1;\nsetp.lt.u32 p, n, 8192;\n@p bra W;\nD:\n}" ::"r"(b), "r"(ph) : "memory");
}
__device__ __forceinline__ void mbar_spin(uint32_t b, uint32_t ph) {
  asm volatile("{\n.reg .pred p;\n.reg .u32 n;\nmov.u32 n, 0;\n"
               "W: mbarrier.test_wait.parity.shared::cta.b64 p, [%0], %1;\n@p bra D;\nnanosleep.u32 40;\n"
               "add.u32 n, n, 1;\nsetp.lt.u32 p, n, 100000;\n@p bra W;\nD:\n}" ::"r"(b), "r"(ph) : "memory");
}
#define PWAIT mbar_wait
__device__ __forceinline__ void mbar_wait_cluster(uint32_t b, uint32_t ph) {
  asm volatile("{\n.reg .pred p;\n.reg .u32 n;\nmov.u32 n, 0;\n"
               "W: mbarrier.try_wait.parity.acquire.cluster.shared::cta.b64 p, [%0], %1;\n@p bra D;\n"
               "add.u32 n, n, 1;\nsetp.lt.u32 p, n, 8192;\n@p bra W;\nD:\n}" ::"r"(b), "r"(ph) : "memory");
}
__device__ __forceinline__ void bar_sync(int id, int n) { asm volatile("bar.sync %0, %1;" ::"r"(id), "r"(n) : "memory"); }
__device__ __forceinline__ void bar_arrive(int id, int n) { asm volatile("bar.arrive %0, %1;" ::"r"(id), "r"(n) : "memory"); }
__device__ __forceinline__ unsigned next_tag(unsigned e) { unsigned t; asm volatile("add.u32 %0, %1, 1;" : "=r"(t) : "r"(e) : "memory"); return t; }
__device__ __forceinline__ void fence_async_smem() { asm volatile("fence.proxy.async.shared::cta;" ::: "memory"); }
__device__ __forceinline__ void tma2d(uint32_t dst, const CUtensorMap* tm, int c0, int c1, uint32_t bar) {
  asm volatile("cp.async.bulk.tensor.2d.shared::cluster.global.mbarrier::complete_tx::bytes [%0], [%1, {%3, %4}], [%2];"
               ::"r"(dst), "l"(tm), "r"(bar), "r"(c0), "r"(c1) : "memory");
}
__device__ __forceinline__ void tma2d_mc(uint32_t dst, const CUtensorMap* tm, int c0, int c1, uint32_t bar) {
  asm volatile("cp.async.bulk.tensor.2d.shared::cluster.global.mbarrier::complete_tx::bytes.multicast::cluster [%0], [%1, {%3, %4}], [%2], %5;"
               ::"r"(dst), "l"(tm), "r"(bar), "r"(c0), "r"(c1), "h"((uint16_t)3) : "memory");
}
__device__ __forceinline__ void tma3d_mc(uint32_t dst, const CUtensorMap* tm, int c0, int c1, int c2, uint32_t bar) {
  asm volatile("cp.async.bulk.tensor.3d.shared::cluster.global.mbarrier::complete_tx::bytes.multicast::cluster [%0], [%1, {%3, %4, %5}], [%2], %6;"
               ::"r"(dst), "l"(tm), "r"(bar), "r"(c0), "r"(c1), "r"(c2), "h"((uint16_t)3) : "memory");
}
__device__ __forceinline__ void l2_prefetch(const void* p, uint32_t bytes) { asm volatile("cp.async.bulk.prefetch.L2.global [%0], %1;" ::"l"(p), "r"(bytes) : "memory"); }
__device__ __forceinline__ uint4 ld_try(const uint4* p) {
  uint4 v;
  asm volatile("ld.global.v4.u32 {%0,%1,%2,%3}, [%4];" : "=r"(v.x), "=r"(v.y), "=r"(v.z), "=r"(v.w) : "l"(p) : "memory");
  return v;
}
__device__ __forceinline__ void st_tag(unsigned tag, uint4* p, uint4 v) {
  asm volatile("{\n.reg .b64 lo, hi;\n.reg .b128 v;\n.reg .b32 w;\nlop3.b32 w, %4, %5, 1, 0xD8;\n"
               "mov.b64 lo, {%1, %2};\nmov.b64 hi, {%3, w};\nmov.b128 v, {lo, hi};\nst.relaxed.gpu.global.b128 [%0], v;\n}"
               ::"l"(p), "r"(v.x), "r"(v.y), "r"(v.z), "r"(v.w), "r"(tag) : "memory");
}
__device__ __forceinline__ void st_tag_if(bool c, unsigned tag, uint4* p, uint4 v) {
  asm volatile("{\n.reg .pred p;\n.reg .b64 lo, hi;\n.reg .b128 v;\n.reg .b32 w;\nsetp.ne.u32 p, %6, 0;\nlop3.b32 w, %4, %5, 1, 0xD8;\n"
               "mov.b64 lo, {%1, %2};\nmov.b64 hi, {%3, w};\nmov.b128 v, {lo, hi};\n@p st.relaxed.gpu.global.b128 [%0], v;\n}"
               ::"l"(p), "r"(v.x), "r"(v.y), "r"(v.z), "r"(v.w), "r"(tag), "r"((uint32_t)c) : "memory");
}
__device__ __forceinline__ ulonglong2 ld_rlx2(const void* p) {
  ulonglong2 v;
  asm volatile("ld.relaxed.gpu.global.v2.b64 {%0,%1}, [%2];" : "=l"(v.x), "=l"(v.y) : "l"(p) : "memory");
  return v;
}
__device__ __forceinline__ void st_rlx2(void* p, unsigned long long a, unsigned long long b) {
  asm volatile("st.relaxed.gpu.global.v2.b64 [%0], {%1,%2};" ::"l"(p), "l"(a), "l"(b) : "memory");
}
__device__ __forceinline__ unsigned clock32() { unsigned c; asm volatile("mov.u32 %0, %%clock;" : "=r"(c)); return c; }
__device__ __forceinline__ uint4 ldg128(const void* p) {
  uint4 v;
  asm volatile("ld.global.nc.v4.u32 {%0,%1,%2,%3}, [%4];" : "=r"(v.x), "=r"(v.y), "=r"(v.z), "=r"(v.w) : "l"(p));
  return v;
}
__device__ __forceinline__ uint4 lds128(uint32_t a) {
  uint4 v;
  asm volatile("ld.shared.v4.u32 {%0,%1,%2,%3}, [%4];" : "=r"(v.x), "=r"(v.y), "=r"(v.z), "=r"(v.w) : "r"(a));
  return v;
}
__device__ __forceinline__ uint32_t lds32(uint32_t a) { uint32_t v; asm volatile("ld.shared.u32 %0, [%1];" : "=r"(v) : "r"(a)); return v; }
__device__ __forceinline__ void sts32(uint32_t a, uint32_t v) { asm volatile("st.shared.u32 [%0], %1;" ::"r"(a), "r"(v) : "memory"); }
__device__ __forceinline__ void sts128f(uint32_t a, float x, float y, float z, float w) {
  asm volatile("st.shared.v4.f32 [%0], {%1,%2,%3,%4};" ::"r"(a), "f"(x), "f"(y), "f"(z), "f"(w) : "memory");
}
__device__ __forceinline__ void ldsm4(uint32_t (&r)[4], uint32_t a) {
  asm volatile("ldmatrix.sync.aligned.m8n8.x4.shared.b16 {%0,%1,%2,%3}, [%4];" : "=r"(r[0]), "=r"(r[1]), "=r"(r[2]), "=r"(r[3]) : "r"(a));
}
__device__ __forceinline__ void ldsm4t(uint32_t (&r)[4], uint32_t a) {
  asm volatile("ldmatrix.sync.aligned.m8n8.x4.trans.shared.b16 {%0,%1,%2,%3}, [%4];" : "=r"(r[0]), "=r"(r[1]), "=r"(r[2]), "=r"(r[3]) : "r"(a));
}
__device__ __forceinline__ void stsm4(uint32_t a, uint32_t r0, uint32_t r1, uint32_t r2, uint32_t r3) {
  asm volatile("stmatrix.sync.aligned.m8n8.x4.shared.b16 [%0], {%1,%2,%3,%4};" ::"r"(a), "r"(r0), "r"(r1), "r"(r2), "r"(r3) : "memory");
}
__device__ __forceinline__ void mma16816(float* d, uint32_t a0, uint32_t a1, uint32_t a2, uint32_t a3, uint32_t b0, uint32_t b1) {
  asm("mma.sync.aligned.m16n8k16.row.col.f32.bf16.bf16.f32 {%0,%1,%2,%3}, {%4,%5,%6,%7}, {%8,%9}, {%0,%1,%2,%3};"
      : "+f"(d[0]), "+f"(d[1]), "+f"(d[2]), "+f"(d[3]) : "r"(a0), "r"(a1), "r"(a2), "r"(a3), "r"(b0), "r"(b1));
}
__device__ __forceinline__ void mma1688(float* d, uint32_t a0, uint32_t a1, uint32_t b0) {
  asm("mma.sync.aligned.m16n8k8.row.col.f32.bf16.bf16.f32 {%0,%1,%2,%3}, {%4,%5}, {%6}, {%0,%1,%2,%3};"
      : "+f"(d[0]), "+f"(d[1]), "+f"(d[2]), "+f"(d[3]) : "r"(a0), "r"(a1), "r"(b0));
}
__device__ __forceinline__ void mma16816_z(float* d, uint32_t a0, uint32_t a1, uint32_t a2, uint32_t a3, uint32_t b0, uint32_t b1) {
  asm("mma.sync.aligned.m16n8k16.row.col.f32.bf16.bf16.f32 {%0,%1,%2,%3}, {%4,%5,%6,%7}, {%8,%9}, {%10,%10,%10,%10};"
      : "=f"(d[0]), "=f"(d[1]), "=f"(d[2]), "=f"(d[3]) : "r"(a0), "r"(a1), "r"(a2), "r"(a3), "r"(b0), "r"(b1), "f"(0.f));
}
__device__ __forceinline__ uint32_t pack2(float lo, float hi) { uint32_t r; asm("cvt.rn.bf16x2.f32 %0, %1, %2;" : "=r"(r) : "f"(hi), "f"(lo)); return r; }
__device__ __forceinline__ float bf_lo(uint32_t w) { return __uint_as_float(w << 16); }
__device__ __forceinline__ float bf_hi(uint32_t w) { return __uint_as_float(w & 0xFFFF0000u); }
__device__ __forceinline__ float bf_round(float x) { return __bfloat162float(__float2bfloat16_rn(x)); }
__device__ __forceinline__ uint32_t hfma2(uint32_t a, uint32_t b, uint32_t c) { uint32_t r; asm("fma.rn.bf16x2 %0, %1, %2, %3;" : "=r"(r) : "r"(a), "r"(b), "r"(c)); return r; }
__device__ __forceinline__ float ex2(float x) { float y; asm("ex2.approx.ftz.f32 %0, %1;" : "=f"(y) : "f"(x)); return y; }
struct RowNorm { uint32_t hi, c; };
__device__ __forceinline__ RowNorm make_norm(float mean, float rstd) {
  RowNorm n;
  const float h = bf_round(rstd);
  n.hi = pack2(h, h);
  n.c = pack2(-mean * h, -mean * h);
  return n;
}
__device__ __forceinline__ uint32_t norm1(uint32_t w, const RowNorm& n) { return hfma2(w, n.hi, n.c); }
__device__ __forceinline__ uint64_t mkdesc(uint32_t lo) {
  uint64_t d;
  asm("mov.b64 %0, {%1, %2};" : "=l"(d) : "r"(lo), "r"(0x40000040u));
  return d;
}
__device__ __forceinline__ void wg_fence() { asm volatile("wgmma.fence.sync.aligned;" ::: "memory"); }
__device__ __forceinline__ void wg_commit() { asm volatile("wgmma.commit_group.sync.aligned;" ::: "memory"); }
template <int N> __device__ __forceinline__ void wg_wait() { asm volatile("wgmma.wait_group.sync.aligned %0;" ::"n"(N) : "memory"); }
template <int N> __device__ __forceinline__ void pin(float (&d)[N]) {
#pragma unroll
  for (int i = 0; i < N; i++) asm volatile("" : "+f"(d[i])::"memory");
}
__device__ __forceinline__ float silu_bf(float c) { return bf_round(__fdividef(c, 1.f + __expf(-c))); }

__device__ __forceinline__ void wgmma_rs_n48_z(float (&d)[24], uint32_t a0, uint32_t a1, uint32_t a2, uint32_t a3, uint64_t desc) {
  asm volatile(
    "wgmma.mma_async.sync.aligned.m64n48k16.f32.bf16.bf16 "
    "{%0, %1, %2, %3, %4, %5, %6, %7, %8, %9, %10, %11, %12, %13, %14, %15, "
    "%16, %17, %18, %19, %20, %21, %22, %23}, "
    "{%24, %25, %26, %27}, %28, 0, 1, 1, 1;"
    : "=f"(d[0]), "=f"(d[1]), "=f"(d[2]), "=f"(d[3]), "=f"(d[4]), "=f"(d[5]), "=f"(d[6]), "=f"(d[7]),
      "=f"(d[8]), "=f"(d[9]), "=f"(d[10]), "=f"(d[11]), "=f"(d[12]), "=f"(d[13]), "=f"(d[14]), "=f"(d[15]),
      "=f"(d[16]), "=f"(d[17]), "=f"(d[18]), "=f"(d[19]), "=f"(d[20]), "=f"(d[21]), "=f"(d[22]), "=f"(d[23])
    : "r"(a0), "r"(a1), "r"(a2), "r"(a3), "l"(desc));
}

__device__ __forceinline__ void wgmma_rs_n48_a(float (&d)[24], uint32_t a0, uint32_t a1, uint32_t a2, uint32_t a3, uint64_t desc) {
  asm volatile(
    "wgmma.mma_async.sync.aligned.m64n48k16.f32.bf16.bf16 "
    "{%0, %1, %2, %3, %4, %5, %6, %7, %8, %9, %10, %11, %12, %13, %14, %15, "
    "%16, %17, %18, %19, %20, %21, %22, %23}, "
    "{%24, %25, %26, %27}, %28, 1, 1, 1, 1;"
    : "+f"(d[0]), "+f"(d[1]), "+f"(d[2]), "+f"(d[3]), "+f"(d[4]), "+f"(d[5]), "+f"(d[6]), "+f"(d[7]),
      "+f"(d[8]), "+f"(d[9]), "+f"(d[10]), "+f"(d[11]), "+f"(d[12]), "+f"(d[13]), "+f"(d[14]), "+f"(d[15]),
      "+f"(d[16]), "+f"(d[17]), "+f"(d[18]), "+f"(d[19]), "+f"(d[20]), "+f"(d[21]), "+f"(d[22]), "+f"(d[23])
    : "r"(a0), "r"(a1), "r"(a2), "r"(a3), "l"(desc));
}

__device__ __forceinline__ void wgmma_rs_n48(float (&d)[24], uint32_t a0, uint32_t a1, uint32_t a2, uint32_t a3, uint64_t desc, bool acc) {
  if (acc) wgmma_rs_n48_a(d, a0, a1, a2, a3, desc); else wgmma_rs_n48_z(d, a0, a1, a2, a3, desc);
}

__device__ __forceinline__ void wgmma_rs_n64_z(float (&d)[32], uint32_t a0, uint32_t a1, uint32_t a2, uint32_t a3, uint64_t desc) {
  asm volatile(
    "wgmma.mma_async.sync.aligned.m64n64k16.f32.bf16.bf16 "
    "{%0, %1, %2, %3, %4, %5, %6, %7, %8, %9, %10, %11, %12, %13, %14, %15, "
    "%16, %17, %18, %19, %20, %21, %22, %23, %24, %25, %26, %27, %28, %29, %30, %31}, "
    "{%32, %33, %34, %35}, %36, 0, 1, 1, 1;"
    : "=f"(d[0]), "=f"(d[1]), "=f"(d[2]), "=f"(d[3]), "=f"(d[4]), "=f"(d[5]), "=f"(d[6]), "=f"(d[7]),
      "=f"(d[8]), "=f"(d[9]), "=f"(d[10]), "=f"(d[11]), "=f"(d[12]), "=f"(d[13]), "=f"(d[14]), "=f"(d[15]),
      "=f"(d[16]), "=f"(d[17]), "=f"(d[18]), "=f"(d[19]), "=f"(d[20]), "=f"(d[21]), "=f"(d[22]), "=f"(d[23]),
      "=f"(d[24]), "=f"(d[25]), "=f"(d[26]), "=f"(d[27]), "=f"(d[28]), "=f"(d[29]), "=f"(d[30]), "=f"(d[31])
    : "r"(a0), "r"(a1), "r"(a2), "r"(a3), "l"(desc));
}

__device__ __forceinline__ void wgmma_rs_n64_a(float (&d)[32], uint32_t a0, uint32_t a1, uint32_t a2, uint32_t a3, uint64_t desc) {
  asm volatile(
    "wgmma.mma_async.sync.aligned.m64n64k16.f32.bf16.bf16 "
    "{%0, %1, %2, %3, %4, %5, %6, %7, %8, %9, %10, %11, %12, %13, %14, %15, "
    "%16, %17, %18, %19, %20, %21, %22, %23, %24, %25, %26, %27, %28, %29, %30, %31}, "
    "{%32, %33, %34, %35}, %36, 1, 1, 1, 1;"
    : "+f"(d[0]), "+f"(d[1]), "+f"(d[2]), "+f"(d[3]), "+f"(d[4]), "+f"(d[5]), "+f"(d[6]), "+f"(d[7]),
      "+f"(d[8]), "+f"(d[9]), "+f"(d[10]), "+f"(d[11]), "+f"(d[12]), "+f"(d[13]), "+f"(d[14]), "+f"(d[15]),
      "+f"(d[16]), "+f"(d[17]), "+f"(d[18]), "+f"(d[19]), "+f"(d[20]), "+f"(d[21]), "+f"(d[22]), "+f"(d[23]),
      "+f"(d[24]), "+f"(d[25]), "+f"(d[26]), "+f"(d[27]), "+f"(d[28]), "+f"(d[29]), "+f"(d[30]), "+f"(d[31])
    : "r"(a0), "r"(a1), "r"(a2), "r"(a3), "l"(desc));
}

__device__ __forceinline__ void wgmma_rs_n64(float (&d)[32], uint32_t a0, uint32_t a1, uint32_t a2, uint32_t a3, uint64_t desc, bool acc) {
  if (acc) wgmma_rs_n64_a(d, a0, a1, a2, a3, desc); else wgmma_rs_n64_z(d, a0, a1, a2, a3, desc);
}

__device__ __forceinline__ void wgmma_rs_n128_z(float (&d)[64], uint32_t a0, uint32_t a1, uint32_t a2, uint32_t a3, uint64_t desc) {
  asm volatile(
    "wgmma.mma_async.sync.aligned.m64n128k16.f32.bf16.bf16 "
    "{%0, %1, %2, %3, %4, %5, %6, %7, %8, %9, %10, %11, %12, %13, %14, %15, "
    "%16, %17, %18, %19, %20, %21, %22, %23, %24, %25, %26, %27, %28, %29, %30, %31, "
    "%32, %33, %34, %35, %36, %37, %38, %39, %40, %41, %42, %43, %44, %45, %46, %47, "
    "%48, %49, %50, %51, %52, %53, %54, %55, %56, %57, %58, %59, %60, %61, %62, %63}, "
    "{%64, %65, %66, %67}, %68, 0, 1, 1, 1;"
    : "=f"(d[0]), "=f"(d[1]), "=f"(d[2]), "=f"(d[3]), "=f"(d[4]), "=f"(d[5]), "=f"(d[6]), "=f"(d[7]),
      "=f"(d[8]), "=f"(d[9]), "=f"(d[10]), "=f"(d[11]), "=f"(d[12]), "=f"(d[13]), "=f"(d[14]), "=f"(d[15]),
      "=f"(d[16]), "=f"(d[17]), "=f"(d[18]), "=f"(d[19]), "=f"(d[20]), "=f"(d[21]), "=f"(d[22]), "=f"(d[23]),
      "=f"(d[24]), "=f"(d[25]), "=f"(d[26]), "=f"(d[27]), "=f"(d[28]), "=f"(d[29]), "=f"(d[30]), "=f"(d[31]),
      "=f"(d[32]), "=f"(d[33]), "=f"(d[34]), "=f"(d[35]), "=f"(d[36]), "=f"(d[37]), "=f"(d[38]), "=f"(d[39]),
      "=f"(d[40]), "=f"(d[41]), "=f"(d[42]), "=f"(d[43]), "=f"(d[44]), "=f"(d[45]), "=f"(d[46]), "=f"(d[47]),
      "=f"(d[48]), "=f"(d[49]), "=f"(d[50]), "=f"(d[51]), "=f"(d[52]), "=f"(d[53]), "=f"(d[54]), "=f"(d[55]),
      "=f"(d[56]), "=f"(d[57]), "=f"(d[58]), "=f"(d[59]), "=f"(d[60]), "=f"(d[61]), "=f"(d[62]), "=f"(d[63])
    : "r"(a0), "r"(a1), "r"(a2), "r"(a3), "l"(desc));
}

__device__ __forceinline__ void wgmma_rs_n128_a(float (&d)[64], uint32_t a0, uint32_t a1, uint32_t a2, uint32_t a3, uint64_t desc) {
  asm volatile(
    "wgmma.mma_async.sync.aligned.m64n128k16.f32.bf16.bf16 "
    "{%0, %1, %2, %3, %4, %5, %6, %7, %8, %9, %10, %11, %12, %13, %14, %15, "
    "%16, %17, %18, %19, %20, %21, %22, %23, %24, %25, %26, %27, %28, %29, %30, %31, "
    "%32, %33, %34, %35, %36, %37, %38, %39, %40, %41, %42, %43, %44, %45, %46, %47, "
    "%48, %49, %50, %51, %52, %53, %54, %55, %56, %57, %58, %59, %60, %61, %62, %63}, "
    "{%64, %65, %66, %67}, %68, 1, 1, 1, 1;"
    : "+f"(d[0]), "+f"(d[1]), "+f"(d[2]), "+f"(d[3]), "+f"(d[4]), "+f"(d[5]), "+f"(d[6]), "+f"(d[7]),
      "+f"(d[8]), "+f"(d[9]), "+f"(d[10]), "+f"(d[11]), "+f"(d[12]), "+f"(d[13]), "+f"(d[14]), "+f"(d[15]),
      "+f"(d[16]), "+f"(d[17]), "+f"(d[18]), "+f"(d[19]), "+f"(d[20]), "+f"(d[21]), "+f"(d[22]), "+f"(d[23]),
      "+f"(d[24]), "+f"(d[25]), "+f"(d[26]), "+f"(d[27]), "+f"(d[28]), "+f"(d[29]), "+f"(d[30]), "+f"(d[31]),
      "+f"(d[32]), "+f"(d[33]), "+f"(d[34]), "+f"(d[35]), "+f"(d[36]), "+f"(d[37]), "+f"(d[38]), "+f"(d[39]),
      "+f"(d[40]), "+f"(d[41]), "+f"(d[42]), "+f"(d[43]), "+f"(d[44]), "+f"(d[45]), "+f"(d[46]), "+f"(d[47]),
      "+f"(d[48]), "+f"(d[49]), "+f"(d[50]), "+f"(d[51]), "+f"(d[52]), "+f"(d[53]), "+f"(d[54]), "+f"(d[55]),
      "+f"(d[56]), "+f"(d[57]), "+f"(d[58]), "+f"(d[59]), "+f"(d[60]), "+f"(d[61]), "+f"(d[62]), "+f"(d[63])
    : "r"(a0), "r"(a1), "r"(a2), "r"(a3), "l"(desc));
}

__device__ __forceinline__ void wgmma_rs_n128(float (&d)[64], uint32_t a0, uint32_t a1, uint32_t a2, uint32_t a3, uint64_t desc, bool acc) {
  if (acc) wgmma_rs_n128_a(d, a0, a1, a2, a3, desc); else wgmma_rs_n128_z(d, a0, a1, a2, a3, desc);
}

__device__ __forceinline__ void arrive_both(uint32_t b, int lane) {
  asm volatile("{\n.reg .pred p;\n.reg .u32 a;\nsetp.lt.u32 p, %1, 2;\n@p mapa.shared::cluster.u32 a, %0, %1;\n"
               "@p mbarrier.arrive.shared::cluster.b64 _, [a];\n}" ::"r"(b), "r"(lane) : "memory");
}
template <int N, int STRIDE> struct Val;
template <int STRIDE> struct Val<3, STRIDE> {
  static __device__ __forceinline__ void run(uint4* a, const uint4* p, unsigned par) {
    asm volatile(
      "{\n"
      ".reg .pred p, q;\n"
      ".reg .u32 n, t, m;\n"
      "mov.u32 n, 0;\n"
      "V:\n"
      "xor.b32 %3, %3, %14;\n"
      "xor.b32 %7, %7, %14;\n"
      "xor.b32 %11, %11, %14;\n"
      "mov.b32 m, %3;\n"
      "or.b32 m, m, %7;\n"
      "or.b32 m, m, %11;\n"
      "and.b32 m, m, 1;\n"
      "setp.ne.u32 p, m, 0;\n"
      "vote.sync.any.pred p, p, 0xffffffff;\n"
      "@!p bra E;\n"
      "add.u32 n, n, 1;\n"
      "and.b32 t, %3, 1;\n"
      "setp.ne.u32 q, t, 0;\n"
      "xor.b32 %3, %3, %14;\n"
      "@q ld.relaxed.gpu.global.v4.u32 {%0, %1, %2, %3}, [%12+0*%13];\n"
      "and.b32 t, %7, 1;\n"
      "setp.ne.u32 q, t, 0;\n"
      "xor.b32 %7, %7, %14;\n"
      "@q ld.relaxed.gpu.global.v4.u32 {%4, %5, %6, %7}, [%12+1*%13];\n"
      "and.b32 t, %11, 1;\n"
      "setp.ne.u32 q, t, 0;\n"
      "xor.b32 %11, %11, %14;\n"
      "@q ld.relaxed.gpu.global.v4.u32 {%8, %9, %10, %11}, [%12+2*%13];\n"
      "setp.lt.u32 p, n, 8192;\n"
      "@p bra V;\n"
      "E:\n"
      "}\n"
      : "+r"(a[0].x), "+r"(a[0].y), "+r"(a[0].z), "+r"(a[0].w), "+r"(a[1].x), "+r"(a[1].y), "+r"(a[1].z), "+r"(a[1].w), "+r"(a[2].x), "+r"(a[2].y), "+r"(a[2].z), "+r"(a[2].w)
      : "l"(p), "n"(STRIDE * 16), "r"(par) : "memory");
  }
};

template <int STRIDE> struct Val<4, STRIDE> {
  static __device__ __forceinline__ void run(uint4* a, const uint4* p, unsigned par) {
    asm volatile(
      "{\n"
      ".reg .pred p, q;\n"
      ".reg .u32 n, t, m;\n"
      "mov.u32 n, 0;\n"
      "V:\n"
      "xor.b32 %3, %3, %18;\n"
      "xor.b32 %7, %7, %18;\n"
      "xor.b32 %11, %11, %18;\n"
      "xor.b32 %15, %15, %18;\n"
      "mov.b32 m, %3;\n"
      "or.b32 m, m, %7;\n"
      "or.b32 m, m, %11;\n"
      "or.b32 m, m, %15;\n"
      "and.b32 m, m, 1;\n"
      "setp.ne.u32 p, m, 0;\n"
      "vote.sync.any.pred p, p, 0xffffffff;\n"
      "@!p bra E;\n"
      "add.u32 n, n, 1;\n"
      "and.b32 t, %3, 1;\n"
      "setp.ne.u32 q, t, 0;\n"
      "xor.b32 %3, %3, %18;\n"
      "@q ld.relaxed.gpu.global.v4.u32 {%0, %1, %2, %3}, [%16+0*%17];\n"
      "and.b32 t, %7, 1;\n"
      "setp.ne.u32 q, t, 0;\n"
      "xor.b32 %7, %7, %18;\n"
      "@q ld.relaxed.gpu.global.v4.u32 {%4, %5, %6, %7}, [%16+1*%17];\n"
      "and.b32 t, %11, 1;\n"
      "setp.ne.u32 q, t, 0;\n"
      "xor.b32 %11, %11, %18;\n"
      "@q ld.relaxed.gpu.global.v4.u32 {%8, %9, %10, %11}, [%16+2*%17];\n"
      "and.b32 t, %15, 1;\n"
      "setp.ne.u32 q, t, 0;\n"
      "xor.b32 %15, %15, %18;\n"
      "@q ld.relaxed.gpu.global.v4.u32 {%12, %13, %14, %15}, [%16+3*%17];\n"
      "setp.lt.u32 p, n, 8192;\n"
      "@p bra V;\n"
      "E:\n"
      "}\n"
      : "+r"(a[0].x), "+r"(a[0].y), "+r"(a[0].z), "+r"(a[0].w), "+r"(a[1].x), "+r"(a[1].y), "+r"(a[1].z), "+r"(a[1].w), "+r"(a[2].x), "+r"(a[2].y), "+r"(a[2].z), "+r"(a[2].w), "+r"(a[3].x), "+r"(a[3].y), "+r"(a[3].z), "+r"(a[3].w)
      : "l"(p), "n"(STRIDE * 16), "r"(par) : "memory");
  }
};

template <int STRIDE> struct Val<8, STRIDE> {
  static __device__ __forceinline__ void run(uint4* a, const uint4* p, unsigned par) {
    asm volatile(
      "{\n"
      ".reg .pred p, q;\n"
      ".reg .u32 n, t, m;\n"
      "mov.u32 n, 0;\n"
      "V:\n"
      "xor.b32 %3, %3, %34;\n"
      "xor.b32 %7, %7, %34;\n"
      "xor.b32 %11, %11, %34;\n"
      "xor.b32 %15, %15, %34;\n"
      "xor.b32 %19, %19, %34;\n"
      "xor.b32 %23, %23, %34;\n"
      "xor.b32 %27, %27, %34;\n"
      "xor.b32 %31, %31, %34;\n"
      "mov.b32 m, %3;\n"
      "or.b32 m, m, %7;\n"
      "or.b32 m, m, %11;\n"
      "or.b32 m, m, %15;\n"
      "or.b32 m, m, %19;\n"
      "or.b32 m, m, %23;\n"
      "or.b32 m, m, %27;\n"
      "or.b32 m, m, %31;\n"
      "and.b32 m, m, 1;\n"
      "setp.ne.u32 p, m, 0;\n"
      "vote.sync.any.pred p, p, 0xffffffff;\n"
      "@!p bra E;\n"
      "add.u32 n, n, 1;\n"
      "and.b32 t, %3, 1;\n"
      "setp.ne.u32 q, t, 0;\n"
      "xor.b32 %3, %3, %34;\n"
      "@q ld.relaxed.gpu.global.v4.u32 {%0, %1, %2, %3}, [%32+0*%33];\n"
      "and.b32 t, %7, 1;\n"
      "setp.ne.u32 q, t, 0;\n"
      "xor.b32 %7, %7, %34;\n"
      "@q ld.relaxed.gpu.global.v4.u32 {%4, %5, %6, %7}, [%32+1*%33];\n"
      "and.b32 t, %11, 1;\n"
      "setp.ne.u32 q, t, 0;\n"
      "xor.b32 %11, %11, %34;\n"
      "@q ld.relaxed.gpu.global.v4.u32 {%8, %9, %10, %11}, [%32+2*%33];\n"
      "and.b32 t, %15, 1;\n"
      "setp.ne.u32 q, t, 0;\n"
      "xor.b32 %15, %15, %34;\n"
      "@q ld.relaxed.gpu.global.v4.u32 {%12, %13, %14, %15}, [%32+3*%33];\n"
      "and.b32 t, %19, 1;\n"
      "setp.ne.u32 q, t, 0;\n"
      "xor.b32 %19, %19, %34;\n"
      "@q ld.relaxed.gpu.global.v4.u32 {%16, %17, %18, %19}, [%32+4*%33];\n"
      "and.b32 t, %23, 1;\n"
      "setp.ne.u32 q, t, 0;\n"
      "xor.b32 %23, %23, %34;\n"
      "@q ld.relaxed.gpu.global.v4.u32 {%20, %21, %22, %23}, [%32+5*%33];\n"
      "and.b32 t, %27, 1;\n"
      "setp.ne.u32 q, t, 0;\n"
      "xor.b32 %27, %27, %34;\n"
      "@q ld.relaxed.gpu.global.v4.u32 {%24, %25, %26, %27}, [%32+6*%33];\n"
      "and.b32 t, %31, 1;\n"
      "setp.ne.u32 q, t, 0;\n"
      "xor.b32 %31, %31, %34;\n"
      "@q ld.relaxed.gpu.global.v4.u32 {%28, %29, %30, %31}, [%32+7*%33];\n"
      "setp.lt.u32 p, n, 8192;\n"
      "@p bra V;\n"
      "E:\n"
      "}\n"
      : "+r"(a[0].x), "+r"(a[0].y), "+r"(a[0].z), "+r"(a[0].w), "+r"(a[1].x), "+r"(a[1].y), "+r"(a[1].z), "+r"(a[1].w), "+r"(a[2].x), "+r"(a[2].y), "+r"(a[2].z), "+r"(a[2].w), "+r"(a[3].x), "+r"(a[3].y), "+r"(a[3].z), "+r"(a[3].w), "+r"(a[4].x), "+r"(a[4].y), "+r"(a[4].z), "+r"(a[4].w), "+r"(a[5].x), "+r"(a[5].y), "+r"(a[5].z), "+r"(a[5].w), "+r"(a[6].x), "+r"(a[6].y), "+r"(a[6].z), "+r"(a[6].w), "+r"(a[7].x), "+r"(a[7].y), "+r"(a[7].z), "+r"(a[7].w)
      : "l"(p), "n"(STRIDE * 16), "r"(par) : "memory");
  }
};

template <int N, int STRIDE> __device__ __forceinline__ void validate(uint4* a, const uint4* p, unsigned tag) { Val<N, STRIDE>::run(a, p, tag & 1); }

__device__ __forceinline__ int fi(float x) { return __float_as_int(x); }

__device__ __forceinline__ uint32_t hadd2(uint32_t a, uint32_t b) { uint32_t r; asm("add.rn.bf16x2 %0, %1, %2;" : "=r"(r) : "r"(a), "r"(b)); return r; }
__device__ __forceinline__ uint32_t packt(float lo, float hi) { return __byte_perm(__float_as_uint(lo), __float_as_uint(hi), 0x7632); }
__device__ __forceinline__ void mma16816_c(float* d, const uint32_t* a, uint32_t b0, uint32_t b1, const float* c) {
  asm("mma.sync.aligned.m16n8k16.row.col.f32.bf16.bf16.f32 {%0,%1,%2,%3}, {%4,%5,%6,%7}, {%8,%9}, {%10,%11,%12,%13};"
      : "=f"(d[0]), "=f"(d[1]), "=f"(d[2]), "=f"(d[3])
      : "r"(a[0]), "r"(a[1]), "r"(a[2]), "r"(a[3]), "r"(b0), "r"(b1), "f"(c[0]), "f"(c[1]), "f"(c[2]), "f"(c[3]));
}
__device__ __forceinline__ void qk_block(float* s, const uint32_t* qf, uint32_t addr, const float* c) {
  uint32_t kf[4];
  ldsm4(kf, addr);
  mma16816_c(s, qf, kf[0], kf[1], c);
  mma16816_c(s + 4, qf, kf[2], kf[3], c);
}
__device__ __forceinline__ void qk_edge(float* s, const uint32_t* qf, uint32_t kaddr, bool p0, bool p1) {
  float d[8];
  const float z[4] = {};
  qk_block(s, qf, kaddr, z);
  qk_block(d, qf, kaddr + 16 * 2048, z);
  s[0] = p0 ? s[0] : d[0];
  s[1] = p1 ? s[1] : d[1];
  s[2] = d[2];
  s[3] = d[3];
  s[6] = p0 ? s[6] : d[6];
  s[7] = p1 ? s[7] : d[7];
}
__device__ __forceinline__ void max_block(float& m0, float& m1, const float* s) {
  m0 = fmaxf(fmaxf(m0, s[0]), fmaxf(s[1], fmaxf(s[4], s[5])));
  m1 = fmaxf(fmaxf(m1, s[2]), fmaxf(s[3], fmaxf(s[6], s[7])));
}
__device__ __forceinline__ void edge_offset(float* e, float m0, float m1, float& n0, float& n1) {
  max_block(m0, m1, e);
  m0 = fmaxf(m0, __shfl_xor_sync(0xffffffffu, m0, 1)); m1 = fmaxf(m1, __shfl_xor_sync(0xffffffffu, m1, 1));
  m0 = fmaxf(m0, __shfl_xor_sync(0xffffffffu, m0, 2)); m1 = fmaxf(m1, __shfl_xor_sync(0xffffffffu, m1, 2));
  n0 = -m0; n1 = -m1;
#pragma unroll
  for (int k = 0; k < 8; k++) e[k] += (k & 2) ? n1 : n0;
}
__device__ __forceinline__ void exp_block(uint32_t* pa, const float* s) {
#pragma unroll
  for (int k = 0; k < 4; k++) pa[k] = packt(ex2(s[2 * k]), ex2(s[2 * k + 1]));
}
__device__ __forceinline__ void pv_edge(float* o0, float* o1, const uint32_t* pa, uint32_t va, uint32_t msk) {
  uint32_t vf[4];
  ldsm4t(vf, va);
  mma16816_z(o0, pa[0] & msk, 0u, pa[2], pa[3] & msk, vf[0], vf[1]);
  mma16816_z(o1, pa[0] & msk, 0u, pa[2], pa[3] & msk, vf[2], vf[3]);
  ldsm4t(vf, va + 16 * 2048);
  mma16816(o0, pa[0] & ~msk, pa[1], 0u, pa[3] & ~msk, vf[0], vf[1]);
  mma16816(o1, pa[0] & ~msk, pa[1], 0u, pa[3] & ~msk, vf[2], vf[3]);
}
__device__ __forceinline__ void pv_block(float* o0, float* o1, const uint32_t* pa, uint32_t va) {
  uint32_t vf[4];
  ldsm4t(vf, va);
  mma16816(o0, pa[0], pa[1], pa[2], pa[3], vf[0], vf[1]);
  mma16816(o1, pa[0], pa[1], pa[2], pa[3], vf[2], vf[3]);
}
__device__ __forceinline__ uint4 attn_out(const float* o0, const float* o1, const float* l) {
  float i0, i1;
  asm("rcp.approx.ftz.f32 %0, %1;" : "=f"(i0) : "f"(l[0]));
  asm("rcp.approx.ftz.f32 %0, %1;" : "=f"(i1) : "f"(l[2]));
  return make_uint4(pack2(o0[0] * i0, o0[1] * i0), pack2(o0[2] * i1, o0[3] * i1), pack2(o1[0] * i0, o1[1] * i0), pack2(o1[2] * i1, o1[3] * i1));
}

__device__ __forceinline__ bool tag_ok(const ulonglong2& a, unsigned tag) { return (unsigned)(a.x >> 32) == tag && (unsigned)(a.y >> 32) == tag; }
__device__ __forceinline__ float lo_f(unsigned long long v) { return __uint_as_float((unsigned)v); }

template <bool V> struct BoolC { static constexpr bool value = V; };

__global__ void __cluster_dims__(2, 1, 1) __launch_bounds__(kThreads, 1)
fused_block_kernel(Scratch* __restrict__ S, const __nv_bfloat16* __restrict__ gx, const __nv_bfloat16* __restrict__ gwmod,
                   const __nv_bfloat16* __restrict__ gc, __nv_bfloat16* __restrict__ gout, const __grid_constant__ Params P) {
  extern __shared__ __align__(1024) uint8_t smem[];
  const uint32_t sb = (uint32_t)__cvta_generic_to_shared(smem);
  const int tid = threadIdx.x, lane = tid & 31;
  const int warp = __shfl_sync(0xffffffffu, tid >> 5, 0);
  const int rank = blockIdx.x & 1;
  int R, g;
  {
    const int t = (int)(blockIdx.x >> 1) - 4;
    if (t < 0) { R = 0; g = 8 + t; }
    else if (t < 32) { R = t & 7; g = t >> 3; }
    else { R = 1 + (t - 32) % 7; g = 4 + (t - 32) / 7; }
  }
  const int r = 2 * R + rank, cta = 8 * r + g;
  const int rd = 2 * R + (g >> 2), gd = 2 * (g & 3) + rank;
  const uint32_t bar = sb + OFF_BAR;

  if (warp >= 8) {
    asm volatile("setmaxnreg.dec.sync.aligned.u32 40;");
    const int aw = warp - 8;
    uint4 wm[4];
    const int au = 32 * aw + lane;
#pragma unroll
    for (int i = 0; i < 4; i++) wm[i] = ldg128(gwmod + (size_t)(64 * g + (au >> 3) + 16 * i) * 3072 + 64 * r + 8 * (au & 7));
    const float cv = __bfloat162float(gc[64 * g + (au >> 3) + 16 * (au & 3)]);
    const unsigned epoch = S->epoch[cta * 32 + lane];
    asm volatile("barrier.cluster.arrive.relaxed.aligned;" ::: "memory");
    FINE(256, 96);
    {
      const float sv = silu_bf(cv);
      float v[8] = {};
#pragma unroll
      for (int i = 0; i < 4; i++) {
        const float sc = __shfl_sync(0xffffffffu, sv, (lane & 24) + i);
        const uint32_t* a = reinterpret_cast<const uint32_t*>(&wm[i]);
#pragma unroll
        for (int k = 0; k < 4; k++) { v[2 * k] = fmaf(sc, bf_lo(a[k]), v[2 * k]); v[2 * k + 1] = fmaf(sc, bf_hi(a[k]), v[2 * k + 1]); }
      }
      bool up = lane & 16;
#pragma unroll
      for (int i = 0; i < 4; i++) { const float snd = up ? v[i] : v[i + 4], kp = up ? v[i + 4] : v[i]; v[i] = kp + __shfl_xor_sync(0xffffffffu, snd, 16); }
      up = lane & 8;
#pragma unroll
      for (int i = 0; i < 2; i++) { const float snd = up ? v[i] : v[i + 2], kp = up ? v[i + 2] : v[i]; v[i] = kp + __shfl_xor_sync(0xffffffffu, snd, 8); }
      const int col = 8 * (lane & 7) + 2 * (lane >> 3);
      sts32(sb + OFF_TAB + (aw * 64 + col) * 4, __float_as_uint(v[0]));
      sts32(sb + OFF_TAB + (aw * 64 + col + 1) * 4, __float_as_uint(v[1]));
    }
    bar_sync(2, 128);
    const unsigned tag = next_tag(epoch);
    if (aw == 1 && lane < 16) {
      float t0 = 0.f, t1 = 0.f, t2 = 0.f, t3 = 0.f;
#pragma unroll
      for (int i = 0; i < 4; i++) {
        const uint4 p = lds128(sb + OFF_TAB + i * 256 + lane * 16);
        t0 += __uint_as_float(p.x); t1 += __uint_as_float(p.y); t2 += __uint_as_float(p.z); t3 += __uint_as_float(p.w);
      }
      st_tag(tag, reinterpret_cast<uint4*>(&S->mod1[g][64 * r + 4 * lane]),
             make_uint4(__float_as_uint(t0), __float_as_uint(t1), __float_as_uint(t2), __float_as_uint(t3)));
    }
    FINE(288, 97);
    bar_sync(4, 384);
    if (aw == 3) S->epoch[cta * 32 + lane] = tag;
    if (aw == 1) {
      if (lane < 2) mbar_expect(bar + 8 * (B_RED + lane), 16384);
      mbar_wait(bar + 8 * B_VN, 0);
      if (lane < 3) l2_prefetch(reinterpret_cast<const uint8_t*>((&P.wg)[lane]) + cta * 11008, 11008);
    } else if (aw == 2) {
      if (lane < 3) mbar_expect(bar + 8 * (B_WKV + 3 + lane), 32768);
      mbar_wait(bar + 8 * B_XFREE, 0);
      if (lane == 0) tma2d_mc(sb + kv_off(3) + rank * kv_lbo(3), &P.tm_qkv, 512 + 512 * rank + 64 * g, 384, bar + 8 * (B_WKV + 3));
      else if (lane < 3) {
        const int i = 2 * (lane - 1) + rank;
        tma2d_mc(sb + OFF_WQ + i * 2 * U, &P.tm_qkv, 64 * g, 128 * i, bar + 8 * (B_WKV + 3 + lane));
      }
      if (lane == 4) l2_prefetch(reinterpret_cast<const uint8_t*>(P.wo) + cta * 4096, 4096);
    } else {
      const int u = (aw == 0 ? 0 : 32) + lane;
      mbar_wait(bar + 8 * B_XFREE, 0);
      const __nv_bfloat16* wp = gwmod + (size_t)(64 * g + (u >> 4)) * 3072 + 1024 + 128 * r + 8 * (u & 15);
      const float sv = silu_bf(__bfloat162float(gc[64 * g + (u >> 4) + 4 * (u & 15)]));
      float acc[8];
#pragma unroll
      for (int i = 0; i < 8; i++) acc[i] = 0.f;
#pragma unroll 1
      for (int bt = 0; bt < 4; bt++) {
        uint4 w[4];
#pragma unroll
        for (int i = 0; i < 4; i++) w[i] = ldg128(wp + (size_t)(bt * 4 + i) * 4 * 3072);
        if (bt == 0) {
#pragma unroll
          for (int i = 4; i < 16; i++) asm volatile("prefetch.global.L1 [%0];" ::"l"(wp + (size_t)i * 4 * 3072));
        }
#pragma unroll
        for (int i = 0; i < 4; i++) {
          const float s = __shfl_sync(0xffffffffu, sv, (lane & 16) + bt * 4 + i);
          const uint32_t* ww = reinterpret_cast<const uint32_t*>(&w[i]);
#pragma unroll
          for (int k = 0; k < 4; k++) {
            acc[2 * k] = fmaf(s, bf_lo(ww[k]), acc[2 * k]);
            acc[2 * k + 1] = fmaf(s, bf_hi(ww[k]), acc[2 * k + 1]);
          }
        }
      }
#pragma unroll
      for (int i = 0; i < 8; i++) acc[i] += __shfl_xor_sync(0xffffffffu, acc[i], 16);
      const int hf = lane >> 4;
      float4 v = hf ? make_float4(acc[4], acc[5], acc[6], acc[7]) : make_float4(acc[0], acc[1], acc[2], acc[3]);
      if (aw == 3) sts128f(sb + OFF_TMP + lane * 16, v.x, v.y, v.z, v.w);
      bar_sync(3, 64);
      if (aw == 0) {
        const uint4 o = lds128(sb + OFF_TMP + lane * 16);
        st_tag(tag, reinterpret_cast<uint4*>(&S->mod2[g][128 * r + 8 * (lane & 15) + 4 * hf]),
               make_uint4((__float_as_uint(v.x + __uint_as_float(o.x))), (__float_as_uint(v.y + __uint_as_float(o.y))),
                          (__float_as_uint(v.z + __uint_as_float(o.z))), (__float_as_uint(v.w + __uint_as_float(o.w)))));
      }
      FINE(352, 120);
    }
    __syncwarp();
    mbar_wait(bar + 8 * B_VN, 0);
    if (aw == 0 && lane == 0) {
      mbar_expect(bar + 8 * B_WO, 65536);
      tma2d(sb + OFF_WV, &P.tm_wo, 64 * gd, 0, bar + 8 * B_WO);
      tma2d(sb + OFF_WV + 4 * U, &P.tm_wo, 64 * gd, 256, bar + 8 * B_WO);
    }
    bar_sync(2, 128);
    {
      const int col = 512 * aw + 64 * gd + 4 * (lane & 15);
      const uint4* mp = reinterpret_cast<const uint4*>(&S->mod2[0][col]);
      float v0 = 0.f, v1 = 0.f, v2 = 0.f, v3 = 0.f;
#pragma unroll 1
      for (int pb = 0; pb < 8; pb += 4) {
        uint4 a[4];
#pragma unroll
        for (int k = 0; k < 4; k++) a[k] = ld_try(mp + (pb + k) * 512);
        validate<4, 512>(a, mp + pb * 512, tag);
#pragma unroll
        for (int k = 0; k < 4; k++) {
          v0 += __uint_as_float(a[k].x); v1 += __uint_as_float(a[k].y); v2 += __uint_as_float(a[k].z); v3 += __uint_as_float(a[k].w);
        }
      }
      const float add = aw == 2 ? 1.f : 0.f;
      sts32(sb + OFF_TMP + 32 * (lane & 15) + 4 * aw, pack2(add + bf_round(v0), add + bf_round(v1)));
      sts32(sb + OFF_TMP + 32 * (lane & 15) + 16 + 4 * aw, pack2(add + bf_round(v2), add + bf_round(v3)));
      __syncwarp();
      if (lane == 0) mbar_arrive(bar + 8 * B_TAB);
      FINE(352, 121);
    }
    asm volatile("barrier.cluster.wait.aligned;" ::: "memory");
    if (aw == 0) {
      const CUtensorMap* tgu = (&P.tm_g0) + (g == 7 ? 1 : 0) + 2 * rank;
      const int sl = g == 7 ? 0 : g;
#pragma unroll 1
      for (int t = 0; t < 18; t++) {
        const int slot = ring_slot(t);
        PWAIT(bar + 8 * (B_EMPTY + slot), (t / 6) & 1);
        if (t >= INFL) PWAIT(bar + 8 * (B_FULL + ring_slot(t - INFL)), ((t - INFL) / 6) & 1);
        const uint32_t dst = sb + slot * STAGE, fb = bar + 8 * (B_FULL + slot);
        if (lane == 0) mbar_expect(fb, 32768);
        __syncwarp();
        if (t < 12) {
          if (lane == 0) tma3d_mc(dst + rank * 16384, tgu, 64 * (t >> 2), sl, 128 * (t & 3), fb);
        } else if (lane < 4) {
          const int ch = 2 * (t - 12) + (lane >> 1);
          const int row = 704 * rank + 176 * (ch & 3) + 64 * (ch >> 2);
          tma2d(dst + lane * 8192, &P.tm_wd, 128 * (g & 3) + 64 * ((lane & 1) ^ rank), row, fb);
        }
      }
    } else if (aw == 1 && lane == 0) {
      mbar_wait(bar + 8 * B_KRDY, 1);
      mbar_expect(bar + 8 * B_XR, 16384);
      tma2d(sb + OFF_RED + 2 * U, &P.tm_x, 64 * gd, 128 * rd, bar + 8 * B_XR);
    }
  } else {
    asm volatile("setmaxnreg.inc.sync.aligned.u32 232;");
    const int wg = warp >> 2, gq = lane >> 2, q = lane & 3;
    const uint32_t db = (sb & 0x3FFFF) >> 4;
    uint32_t qf[16];
    unsigned tag;
    {
      if (lane == 0) {
        if (warp == 0) {
          asm volatile("prefetch.tensormap [%0];" ::"l"(&P.tm_x) : "memory");
          asm volatile("prefetch.tensormap [%0];" ::"l"(&P.tm_qkv) : "memory");
#pragma unroll
          for (int i = B_X; i < B_WKV + 3; i++) mbar_init(bar + 8 * i, 1);
          fence_async_smem();
#pragma unroll
          for (int c = 0; c < 8; c++) {
            if (!(c & 3)) mbar_expect(bar + 8 * (B_X + (c >> 2)), 65536);
            tma2d(sb + OFF_WV + c * 2 * U, &P.tm_x, 64 * c, 128 * r, bar + 8 * (B_X + (c >> 2)));
          }
#pragma unroll
          for (int c = 0; c < 3; c++) {
            mbar_expect(bar + 8 * (B_WKV + c), 32768);
            tma2d(sb + kv_off(c), &P.tm_qkv, 512 + 64 * g, 128 * c, bar + 8 * (B_WKV + c));
            tma2d(sb + kv_off(c) + kv_lbo(c), &P.tm_qkv, 1024 + 64 * g, 128 * c, bar + 8 * (B_WKV + c));
          }
        } else if (warp == 1) {
#pragma unroll
          for (int i = B_WKV + 3; i < B_FULL; i++) mbar_init(bar + 8 * i, i == B_XFREE ? 16 : (i >= B_KRDY ? 8 : (i == B_TAB ? 4 : 1)));
          asm volatile("fence.mbarrier_init.release.cluster;" ::: "memory");
          fence_async_smem();
        } else if (warp == 2) {
#pragma unroll
          for (int i = B_FULL; i < B_COUNT; i++) mbar_init(bar + 8 * i, i >= B_EMPTY ? 16 : 1);
          asm volatile("fence.mbarrier_init.release.cluster;" ::: "memory");
          fence_async_smem();
        }
      } else if (warp == 4 && lane < 7) {
        asm volatile("prefetch.tensormap [%0];" ::"l"(&P.tm_wo + (lane - 1)) : "memory");
      }
      __syncwarp();
      const unsigned epoch = S->epoch[(kCtas + cta) * 32 + lane];
      bar_arrive(4, 384);
      asm volatile("barrier.cluster.arrive.relaxed.aligned;" ::: "memory");
      FINE2(0);
      if (wg == 1) bar_arrive(6, 256);
      bar_sync(1, 256);
      tag = next_tag(epoch);

      if (lane < 16) S->st2[gd][16 * (8 * rd + warp) + lane] = make_uint4(0, 0, 0, 0);
      st_tag(tag + 1, &S->o[((8 * r + warp) * 32 + 4 * g + 3) * 32 + lane], make_uint4(0, 0, 0, 0));
      if (warp == 2) S->epoch[(kCtas + cta) * 32 + lane] = tag;
      FINE2(2);
      uint32_t xa[32][4];
      const uint32_t sw = lane & 7, hi = lane >> 4;
      RowNorm n0, n1;
      {
        float ds[2][4] = {}, g0[2][4] = {}, g1[2][4] = {};
        const uint32_t xrow = sb + OFF_WV + (warp * 16 + (lane & 15)) * 128;
        const uint4* mp = reinterpret_cast<const uint4*>(&S->mod1[0][4 * tid]);
        uint4 a[8];
        mbar_wait(bar + 8 * B_X, 0);
        FINE2(3);
#pragma unroll
        for (int k = 0; k < 32; k++) {
          if (k == 16) {
            mbar_wait(bar + 8 * (B_X + 1), 0);
#pragma unroll
            for (int i = 0; i < 8; i++) a[i] = ld_try(mp + i * 256);
          }
          ldsm4(xa[k], xrow + (k >> 2) * 2 * U + (((2 * (k & 3) + hi) ^ sw) << 4));
          mma16816(ds[k & 1], xa[k][0], xa[k][1], xa[k][2], xa[k][3], 0x3F803F80u, 0x3F803F80u);
          mma1688(g0[0], xa[k][0], xa[k][1], xa[k][0]);
          mma1688(g1[0], xa[k][0], xa[k][1], xa[k][1]);
          mma1688(g0[1], xa[k][2], xa[k][3], xa[k][2]);
          mma1688(g1[1], xa[k][2], xa[k][3], xa[k][3]);
        }
        FINE(0, 116);
            validate<8, 256>(a, mp, tag);
        float v0 = 0.f, v1 = 0.f, v2 = 0.f, v3 = 0.f;
#pragma unroll
        for (int k = 0; k < 8; k++) {
          v0 += __uint_as_float(a[k].x); v1 += __uint_as_float(a[k].y); v2 += __uint_as_float(a[k].z); v3 += __uint_as_float(a[k].w);
        }
        const float add = wg ? 1.f : 0.f;
        const int u = tid & 127;
        const uint32_t td = sb + OFF_TAB + (u >> 2) * 64 + (u & 1) * 32 + ((u >> 1) & 1) * 4 + (wg ? 0 : 8);
        sts32(td, pack2(add + bf_round(v0), add + bf_round(v1)));
        sts32(td + 16, pack2(add + bf_round(v2), add + bf_round(v3)));
        const int dl = (lane & 28) | (gq >> 1);
        const float q0 = __shfl_sync(0xffffffffu, (gq & 1) ? g0[0][1] + g0[1][1] : g0[0][0] + g0[1][0], dl);
        const float q1 = __shfl_sync(0xffffffffu, (gq & 1) ? g1[0][3] + g1[1][3] : g1[0][2] + g1[1][2], dl);
        const float m0 = (ds[0][0] + ds[1][0]) * (1.f / 512.f), m1 = (ds[0][2] + ds[1][2]) * (1.f / 512.f);
        n0 = make_norm(m0, rsqrtf(fmaxf(fmaf(-m0, m0, q0 * (1.f / 512.f)), 0.f) + 1e-5f));
        n1 = make_norm(m1, rsqrtf(fmaxf(fmaf(-m1, m1, q1 * (1.f / 512.f)), 0.f) + 1e-5f));
        FINE2(4);
        asm volatile("barrier.cluster.wait.aligned;" ::: "memory");
        arrive_both(bar + 8 * B_XFREE, lane);
#pragma unroll
        for (int k = 0; k < 8; k++) {
          xa[k][0] = norm1(xa[k][0], n0); xa[k][1] = norm1(xa[k][1], n1);
          xa[k][2] = norm1(xa[k][2], n0); xa[k][3] = norm1(xa[k][3], n1);
        }
        mbar_wait(bar + 8 * B_WKV, 0);
      }
      bar_sync(1, 256);
      FINE2(5);
      const uint32_t trow = sb + (warp * 16 + (lane & 15)) * 128;
      {
        float acc[64];
        uint4 tb[4];
#define MODULATE(K, T)                                                                                                \
  {                                                                                                                   \
    xa[K][0] = hfma2(xa[K][0], (T).x, (T).z); xa[K][1] = hfma2(xa[K][1], (T).x, (T).z);                               \
    xa[K][2] = hfma2(xa[K][2], (T).y, (T).w); xa[K][3] = hfma2(xa[K][3], (T).y, (T).w);                               \
  }
#pragma unroll
        for (int c = 0; c < 4; c++) {
#pragma unroll
          for (int k = 8 * c + (c ? 4 : 0); k < 8 * c + 8; k++) {
            const uint4 t = lds128(sb + OFF_TAB + k * 64 + q * 16);
            MODULATE(k, t);
          }
          if (c > 0) mbar_wait(bar + 8 * (B_WKV + c), 0);
          if (c < 3) {
#pragma unroll
            for (int k = 0; k < 4; k++) tb[k] = lds128(sb + OFF_TAB + (8 * c + 8 + k) * 64 + q * 16);
          }
          bar_sync(6 + wg, 256);
          wg_fence();
#pragma unroll
          for (int k = 0; k < 8; k++)
            wgmma_rs_n128(acc, xa[8 * c + k][0], xa[8 * c + k][1], xa[8 * c + k][2], xa[8 * c + k][3],
                          mkdesc(db + (kv_off(c) >> 4) + ((kv_lbo(c) >> 4) << 16) + k * 128), (c | k) != 0);
          wg_commit();
          wg_wait<1>();
          bar_arrive(7 - wg, 256);
          if (c < 3) {
            const uint32_t after = clock32() & (tag == 0 ? 1u : 0u);
            n0.c ^= after;
            n1.c ^= after;
#pragma unroll
            for (int k = 8 * c + 8; k < 8 * c + 16; k++) {
              xa[k][0] = norm1(xa[k][0], n0); xa[k][1] = norm1(xa[k][1], n1);
              xa[k][2] = norm1(xa[k][2], n0); xa[k][3] = norm1(xa[k][3], n1);
            }
#pragma unroll
            for (int k = 0; k < 4; k++) MODULATE(8 * c + 8 + k, tb[k]);
          }
        }
        wg_wait<0>();
        pin(acc);
        uint4* kdst = &S->kv[cta * 2048 + warp * 128 + lane];
#pragma unroll
        for (int t = 0; t < 8; t++) {
          const uint4 w = make_uint4(pack2(acc[8 * t], acc[8 * t + 1]), pack2(acc[8 * t + 2], acc[8 * t + 3]),
                                     pack2(acc[8 * t + 4], acc[8 * t + 5]), pack2(acc[8 * t + 6], acc[8 * t + 7]) & ~1u);
          st_tag(tag, kdst + (t >> 2) * 1024 + (t & 3) * 32, w);
          stsm4(trow + 4 * U + (t >> 2) * OFF_V + (((2 * (t & 3) + hi) ^ sw) << 4), w.x, w.y, w.z, w.w);
        }
        __syncwarp();
        if (lane == 0) mbar_arrive(bar + 8 * B_KRDY);
      }
      FINE2(6);
      {
        float acc[32];
        const uint4* s2 = &S->kv[r >= 2 ? (cta - 16) * 2048 + warp * 128 + lane : g * 2048 + q];
        const uint4* s1 = &S->kv[r >= 1 ? (cta - 8) * 2048 + warp * 128 + lane : g * 2048 + q];
        uint4 f[4][4];
#pragma unroll
        for (int c = 0; c < 4; c++) {
          if (!(c & 1)) mbar_wait(bar + 8 * (B_WKV + 4 + (c >> 1)), 0);
          wg_fence();
#pragma unroll
          for (int k = 8 * c; k < 8 * c + 8; k++) wgmma_rs_n64(acc, xa[k][0], xa[k][1], xa[k][2], xa[k][3], mkdesc(db + (OFF_WQ >> 4) + k * 128), k > 0);
          wg_commit();
          if (c == KF_C) {
#pragma unroll
            for (int t = 0; t < 4; t++) { f[0][t] = ld_try(s2 + 32 * t); f[1][t] = ld_try(s1 + 32 * t); }
          }
          if (c == VF_C) {
            wg_wait<1>();
#pragma unroll
            for (int t = 0; t < 4; t++) { f[2][t] = ld_try(s2 + 1024 + 32 * t); f[3][t] = ld_try(s1 + 1024 + 32 * t); }
          }
        }
        wg_wait<0>();
        pin(acc);
#pragma unroll
        for (int i = 0; i < 16; i++) qf[i] = pack2(acc[2 * i] * kScale, acc[2 * i + 1] * kScale);
        arrive_both(bar + 8 * (B_EMPTY + 5 + (lane >> 1)), lane < 4 ? (lane & 1) : 2);
        FINE2(8);
        mbar_wait(bar + 8 * B_KRDY, 0);
#pragma unroll
        for (int i = 0; i < 4; i++) {
          validate<4, 32>(f[i], ((i & 1) ? s1 : s2) + (i >> 1) * 1024, tag);
          if (r + (i & 1) < 2) {
#pragma unroll
            for (int t = 0; t < 4; t++) f[i][t] = i < 2 ? make_uint4(f[i][t].x, f[i][t].x, f[i][t].z, f[i][t].z) : make_uint4(0, 0, 0, 0);
          }
#pragma unroll
          for (int t = 0; t < 4; t++)
            stsm4(trow + (i & 1) * 2 * U + (i >> 1) * OFF_V + (((2 * t + hi) ^ sw) << 4), f[i][t].x, f[i][t].y, f[i][t].z, f[i][t].w);
          if (i & 1) {
            __syncwarp();
            if (lane == 0) mbar_arrive(bar + 8 * (B_KN + (i >> 1)));
          }
          if (i == 1) FINE2(7);
        }
      }
    }
    const int rt = 8 * rd + warp, fo = (rt * 32 + 4 * gd) * 32 + lane;
    const uint4* osrc = &S->o[rt * 32 * 32 + lane];
    uint4 oa[32];
    {
      mbar_wait(bar + 8 * B_KN, 0);
      FINE2(9);
      const int b0 = r >= 2 ? 0 : 16 - 8 * r - warp;
      const bool p0 = 2 * q > gq, p1 = 2 * q + 1 > gq;
      const uint32_t msk = (p0 ? 0xFFFFu : 0u) | (p1 ? 0xFFFF0000u : 0u);
      const uint32_t lm = b0 > 0 ? ~msk : ~0u, lo = b0 > 0 ? 0u : ~0u;
      const uint32_t krow = sb + OFF_K + warp * 2048 + ((lane >> 4) * 8 + (lane & 7)) * 128;
      const uint32_t vrow = sb + OFF_V + warp * 2048 + (lane & 15) * 128;
      uint4* dst = &S->o[((8 * r + warp) * 32 + 4 * g) * 32 + lane];
      const uint32_t kc = (lane >> 3) & 1, vc = lane >> 4, sw = lane & 7;
      const uint32_t ones = 0x3F803F80u;
      const int zero = b0 >> 8;
      uint32_t redo = 0;
      float e[8], n0, n1, po0[4] = {}, po1[4] = {}, pl[4] = {1.f, 1.f, 1.f, 1.f};
      qk_edge(e, qf, krow + ((kc ^ sw) << 4), p0, p1);
      edge_offset(e, -INFINITY, -INFINITY, n0, n1);
      mbar_wait(bar + 8 * B_VN, 0);
#pragma unroll
      for (int k = 0; k < 4; k++) st_tag(tag + 1, &S->h2[fo + 32 * k], make_uint4(0, 0, 0, 0));
      FINE2(23);
#define ON(b) ((b) >= b0 ? ones : 0u)
      auto finish = [&](int h) {
        const float t = ((po0[0] + po0[1]) + (po0[2] + po0[3])) + ((po1[0] + po1[1]) + (po1[2] + po1[3]));
        const bool ok = pl[0] < 1e12f && pl[2] < 1e12f && fabsf(t) <= 3e38f;
        const uint4 w = attn_out(po0, po1, pl);
        st_tag_if(ok && h >= 0, tag, dst + 32 * h, w);
        redo |= ok ? 0u : 1u << h;
        return (w.x ^ w.y) ^ (w.z ^ w.w) ^ redo;
      };
      auto head = [&](int h, auto last_c) {
        constexpr bool LAST = decltype(last_c)::value;
        const uint32_t ka = krow + (((2 * h + kc) ^ sw) << 4), kb = krow + (((2 * h + 2 + kc) ^ sw) << 4);
        const uint32_t va = vrow + (((2 * h + vc) ^ sw) << 4);
        const float cq[4] = {n0, __int_as_float(fi(n0) | zero), n1, __int_as_float(fi(n1) | zero)};
        float s[8], o0[4], o1[4], l[4];
        uint32_t pa[4], h0, h1, kd[17], kcur = ka;
        exp_block(pa, e);
        const uint32_t fin = finish(h - 1);
        h0 = hadd2(pa[0] & lm, pa[2] & lo); h1 = hadd2(pa[1], pa[3] & lm);
        pv_edge(o0, o1, pa, va, msk);
        kd[16] = ka | ((fi(o0[0]) ^ fin) & zero);
        qk_block(s, qf, ka + 15 * 2048, cq);
#pragma unroll
        for (int b = 15; b > 0; b--) {
          exp_block(pa, s);
          if (b <= 13 && (b & 1)) kcur = kd[b + 3];
          if (b > 1) qk_block(s, qf, kcur + (b - 1) * 2048, cq);
          if (LAST && (b == PF_B0 || b == PF_B1 || b == PF_B2)) {
            const int hh = b == PF_B0 ? 0 : (b == PF_B1 ? 1 : 2);
#pragma unroll
            for (int k = 0; k < 8; k++) oa[8 * hh + k] = ld_try(osrc + (4 * k + hh) * 32);
#pragma unroll
            for (int k = 0; k < 8; k++) asm volatile("" : "+f"(s[k]));
            mbar_wait(bar + 8 * (b == PF_B0 ? B_WO : B_TAB), 0);
          }
          if (b == 15) mma16816_z(l, h0, h1, hadd2(pa[0], pa[2]), hadd2(pa[1], pa[3]), ones, ON(b));
          else if (b & 1) mma16816(l, h0, h1, hadd2(pa[0], pa[2]), hadd2(pa[1], pa[3]), ON(b + 1), ON(b));
          else { h0 = hadd2(pa[0], pa[2]); h1 = hadd2(pa[1], pa[3]); }
          pv_block(o0, o1, pa, va + b * 2048);
          kd[b] = ka | (fi(o0[0]) & zero);
          if (!LAST && b == 8) {
            qk_edge(e, qf + 4, kb, p0, p1);
            edge_offset(e, -INFINITY, -INFINITY, n0, n1);
            kd[b] |= (fi(n0) ^ fi(n1)) & zero;
          }
        }
#pragma unroll
        for (int i = 0; i < 4; i++) { po0[i] = o0[i]; po1[i] = o1[i]; pl[i] = l[i]; }
        FINE2(10 + h);
      };
      auto rotate = [&]() {
        const uint32_t t0 = qf[0], t1 = qf[1], t2 = qf[2], t3 = qf[3];
#pragma unroll
        for (int i = 0; i < 12; i++) qf[i] = qf[i + 4];
        qf[12] = t0; qf[13] = t1; qf[14] = t2; qf[15] = t3;
      };
#pragma unroll 1
      for (int h = 0; h < 3; h++) {
        head(h, BoolC<false>());
        rotate();
      }
      head(3, BoolC<true>());
      finish(3);
      if (__any_sync(0xffffffffu, redo != 0)) {
#pragma unroll 1
        for (int h = 0; h < 4; h++) {
          rotate();
          if (!__any_sync(0xffffffffu, (redo >> h) & 1)) continue;
          const uint32_t ka = krow + (((2 * h + kc) ^ sw) << 4), va = vrow + (((2 * h + vc) ^ sw) << 4);
          float s[8], m0 = -INFINITY, m1 = -INFINITY;
          uint32_t pa[4];
#pragma unroll 1
          for (int b = 1; b < 16; b++) {
            const float z[4] = {};
            qk_block(s, qf, ka + b * 2048, z);
            max_block(m0, m1, s);
          }
          qk_edge(e, qf, ka, p0, p1);
          edge_offset(e, m0, m1, n0, n1);
          exp_block(pa, e);
          mma16816_z(pl, pa[0] & lm, pa[1], pa[2] & lo, pa[3] & lm, ones, ones);
          pv_edge(po0, po1, pa, va, msk);
#pragma unroll 1
          for (int b = 1; b < 16; b++) {
            const float cq[4] = {n0, n0, n1, n1};
            qk_block(s, qf, ka + b * 2048, cq);
            exp_block(pa, s);
            mma16816(pl, pa[0], pa[1], pa[2], pa[3], ON(b), ON(b));
            pv_block(po0, po1, pa, va + b * 2048);
          }
          if ((redo >> h) & 1) st_tag(tag, dst + 32 * h, attn_out(po0, po1, pl));
        }
      }
    }
    {
      float acc[32];
      uint32_t xr[4][4];
#pragma unroll
      for (int h = 0; h < 4; h++) {
        validate<8, 128>(&oa[8 * h], osrc + 32 * h, tag);
        if (h == 0) {
          fence_async_smem();
          __syncwarp();
          if (lane == 0) mbar_arrive(bar + 8 * B_KRDY);
        }
        if (h == 3) {
          mbar_wait(bar + 8 * B_XR, 0);
#pragma unroll
          for (int k = 0; k < 4; k++) ldsm4(xr[k], sb + OFF_RED + 2 * U + (warp * 16 + (lane & 15)) * 128 + (((2 * k + (lane >> 4)) ^ (lane & 7)) << 4));
        }
        if (h == REL_H) {
          arrive_both(bar + 8 * (B_EMPTY + (lane >> 1)), lane < 6 ? (lane & 1) : 2);
        }
        FINE2(14 + h);
        wg_fence();
#pragma unroll
        for (int s = 0; s < 8; s++)
          wgmma_rs_n64(acc, oa[8 * h + s].x, oa[8 * h + s].y, oa[8 * h + s].z, oa[8 * h + s].w, mkdesc(db + (OFF_WV >> 4) + (4 * s + h) * 128), (h | s) != 0);
        if (h == O3_H) {
#pragma unroll
          for (int i = 24; i < 32; i++) oa[i] = ld_try(osrc + (4 * (i & 7) + 3) * 32);
        }
      }
      wg_commit();
      wg_wait<0>();
      pin(acc);
      FINE2(18);
      float s0 = 0.f, s1 = 0.f;
      uint32_t tsc[8], tsh[8];
#pragma unroll
      for (int t = 0; t < 8; t++) {
        const uint4 tb = lds128(sb + OFF_TMP + (4 * t + q) * 16);
        tsh[t] = tb.y; tsc[t] = tb.z;
        const float gl = bf_lo(tb.x), gh = bf_hi(tb.x);
        const uint32_t xa = xr[t >> 1][2 * (t & 1)], xb = xr[t >> 1][2 * (t & 1) + 1];
        acc[4 * t] = fmaf(gl, acc[4 * t], bf_lo(xa));
        acc[4 * t + 1] = fmaf(gh, acc[4 * t + 1], bf_hi(xa));
        acc[4 * t + 2] = fmaf(gl, acc[4 * t + 2], bf_lo(xb));
        acc[4 * t + 3] = fmaf(gh, acc[4 * t + 3], bf_hi(xb));
        s0 += acc[4 * t] + acc[4 * t + 1];
        s1 += acc[4 * t + 2] + acc[4 * t + 3];
      }
      s0 += __shfl_xor_sync(0xffffffffu, s0, 1); s1 += __shfl_xor_sync(0xffffffffu, s1, 1);
      s0 += __shfl_xor_sync(0xffffffffu, s0, 2); s1 += __shfl_xor_sync(0xffffffffu, s1, 2);
      s0 *= (1.f / 64.f); s1 *= (1.f / 64.f);
      float q0 = 0.f, q1 = 0.f;
#pragma unroll
      for (int t = 0; t < 8; t++) {
        float d;
        d = acc[4 * t] - s0; q0 = fmaf(d, d, q0);
        d = acc[4 * t + 1] - s0; q0 = fmaf(d, d, q0);
        d = acc[4 * t + 2] - s1; q1 = fmaf(d, d, q1);
        d = acc[4 * t + 3] - s1; q1 = fmaf(d, d, q1);
      }
      q0 += __shfl_xor_sync(0xffffffffu, q0, 1); q1 += __shfl_xor_sync(0xffffffffu, q1, 1);
      q0 += __shfl_xor_sync(0xffffffffu, q0, 2); q1 += __shfl_xor_sync(0xffffffffu, q1, 2);
      if (q < 2) {
        const unsigned long long tg = (unsigned long long)tag << 32;
        st_rlx2(&S->st2[gd][16 * rt + gq + 8 * q], tg | __float_as_uint(q == 0 ? s0 : s1), tg | __float_as_uint(q == 0 ? q0 : q1));
      }
      uint32_t xw[16];
#pragma unroll
      for (int i = 0; i < 16; i++) xw[i] = pack2(acc[2 * i], acc[2 * i + 1]);
      FINE2(20);
      const uint4* sp = &S->st2[2 * q][16 * rt + gq];
      ulonglong2 ua, ub, uc, ud;
      int n = 0;
      do {
        ua = ld_rlx2(sp); ub = ld_rlx2(sp + 2048); uc = ld_rlx2(sp + 8); ud = ld_rlx2(sp + 2048 + 8);
      } while (__any_sync(0xffffffffu, !(tag_ok(ua, tag) && tag_ok(ub, tag) && tag_ok(uc, tag) && tag_ok(ud, tag))) && ++n < kSpinLimit);
      FINE2(21);
      const float ma = lo_f(ua.x), mb = lo_f(ub.x), mc = lo_f(uc.x), md = lo_f(ud.x);
      float m0 = ma + mb, m1 = mc + md;
      m0 += __shfl_xor_sync(0xffffffffu, m0, 1); m1 += __shfl_xor_sync(0xffffffffu, m1, 1);
      m0 += __shfl_xor_sync(0xffffffffu, m0, 2); m1 += __shfl_xor_sync(0xffffffffu, m1, 2);
      m0 *= 0.125f; m1 *= 0.125f;
      float v0 = 64.f * ((ma - m0) * (ma - m0) + (mb - m0) * (mb - m0)) + lo_f(ua.y) + lo_f(ub.y);
      float v1 = 64.f * ((mc - m1) * (mc - m1) + (md - m1) * (md - m1)) + lo_f(uc.y) + lo_f(ud.y);
      v0 += __shfl_xor_sync(0xffffffffu, v0, 1); v1 += __shfl_xor_sync(0xffffffffu, v1, 1);
      v0 += __shfl_xor_sync(0xffffffffu, v0, 2); v1 += __shfl_xor_sync(0xffffffffu, v1, 2);
      const float r0 = rsqrtf(v0 * (1.f / 512.f) + 1e-5f), r1 = rsqrtf(v1 * (1.f / 512.f) + 1e-5f);
      const float c0 = -m0 * r0, c1 = -m1 * r1;
      uint32_t hw[16];
#pragma unroll
      for (int i = 0; i < 16; i++) {
        const float rs = (i & 1) ? r1 : r0, cs = (i & 1) ? c1 : c0;
        hw[i] = (hfma2(pack2(fmaf(bf_lo(xw[i]), rs, cs), fmaf(bf_hi(xw[i]), rs, cs)), tsc[i >> 1], tsh[i >> 1]));
      }
#pragma unroll
      for (int k = 0; k < 4; k++) st_tag(tag, &S->h2[fo + 32 * k], make_uint4(hw[4 * k], hw[4 * k + 1], hw[4 * k + 2], hw[4 * k + 3]));
#pragma unroll
      for (int k = 0; k < 4; k++)
        asm volatile("st.shared.v4.u32 [%0], {%1,%2,%3,%4};" ::"r"(sb + OFF_RED + k * 4096 + tid * 16), "r"(xw[4 * k]), "r"(xw[4 * k + 1]), "r"(xw[4 * k + 2]), "r"(xw[4 * k + 3]) : "memory");
      FINE2(22);
    }
    const uint4* hsrc = &S->hh[(rt * 86 + 44 * rank) * 32 + lane];
    uint4 a[3][8], x1[4];
#define DN_VALIDATE(T)                                                                                                \
  {                                                                                                                   \
    uint4* av = a[(T) % 3];                                                                                           \
    if ((T) < 4) {                                                                                                    \
      validate<4, 32>(av, hsrc + dn_step(T, 0) * 32, tag);                                                            \
      validate<4, 32>(av + 4, hsrc + dn_step(T, 4) * 32, tag);                                                        \
    } else {                                                                                                          \
      validate<3, 32>(av, hsrc + dn_step(T, 0) * 32, tag);                                                            \
      validate<3, 32>(av + 4, hsrc + dn_step(T, 4) * 32, tag);                                                        \
    }                                                                                                                 \
  }
    {
      const int rg = 8 * r + warp;
      const uint4* src = &S->h2[rg * 32 * 32 + lane];
      uint4 xa[32];
      {
#pragma unroll
        for (int k = 0; k < 8; k++) xa[k] = ld_try(src + 32 * k);
        validate<8, 32>(&xa[0], src, tag);
#pragma unroll
        for (int k = 8; k < 16; k++) xa[k] = ld_try(src + 32 * k);
      }
      arrive_both(bar + 8 * (B_EMPTY + 3 + (lane >> 1)), lane < 4 ? (lane & 1) : 2);
      FINE2(47);
      const uint32_t dg = db + ((16384 >> 4) << 16);
      uint4* dst = &S->hh[(rg * 86 + 11 * g) * 32 + lane];
#define HH_OUT(G, U, K, OFFS)                                                                                         \
  st_tag(tag, dst + (OFFS) + 32 * (K),                                                                                \
         make_uint4(pack2((G)[8 * (K)] * (U)[8 * (K)], (G)[8 * (K) + 1] * (U)[8 * (K) + 1]),                          \
                    pack2((G)[8 * (K) + 2] * (U)[8 * (K) + 2], (G)[8 * (K) + 3] * (U)[8 * (K) + 3]),                  \
                    pack2((G)[8 * (K) + 4] * (U)[8 * (K) + 4], (G)[8 * (K) + 5] * (U)[8 * (K) + 5]),                  \
                    pack2((G)[8 * (K) + 6] * (U)[8 * (K) + 6], (G)[8 * (K) + 7] * (U)[8 * (K) + 7])))
#define GU_TURN(ACC, FN, C, T)                                                                                        \
  {                                                                                                                   \
    const int slot = ring_slot(T);                                                                                    \
    const uint32_t d = dg + slot * (STAGE >> 4);                                                                      \
    mbar_wait(bar + 8 * (B_FULL + slot), (T) >= 6);                                                                   \
    bar_sync(6 + wg, 256);                                                                                 \
    wg_fence();                                                                                                       \
    _Pragma("unroll") for (int k = 0; k < 8; k++)                                                                     \
      FN(ACC, xa[8 * (C) + k].x, xa[8 * (C) + k].y, xa[8 * (C) + k].z, xa[8 * (C) + k].w, mkdesc(d + k * 128), ((C) | k) != 0); \
    wg_commit();                                                                                                      \
    bar_arrive(7 - wg, 256);                                                                               \
    if ((C) > 0) {                                                                                                    \
      wg_wait<1>();                                                                                                   \
      arrive_both(bar + 8 * (B_EMPTY + ring_slot((T) - 1)), lane);                                                    \
    }                                                                                                                 \
  }
#define GU_END(ACC, T)                                                                                                \
  {                                                                                                                   \
    wg_wait<0>();                                                                                                     \
    pin(ACC);                                                                                                         \
    arrive_both(bar + 8 * (B_EMPTY + ring_slot(T)), lane);                                                            \
  }
#pragma unroll 1
      for (int p = 0; p < 2; p++) {
        float acc[64];
#pragma unroll
        for (int c = 0; c < 4; c++) {
          GU_TURN(acc, wgmma_rs_n128, c, 4 * p + c);
          if (p == 0 && c < 3) validate<8, 32>(&xa[8 * c + 8], src + 256 * c + 256, tag);
          if (p == 0 && c < 2) {
#pragma unroll
            for (int k = 16 + 8 * c; k < 24 + 8 * c; k++) xa[k] = ld_try(src + 32 * k);
          }
          FINE2(24 + 4 * p + c);
        }
        GU_END(acc, 4 * p + 3);
#pragma unroll
        for (int k = 0; k < 4; k++) HH_OUT(acc, acc + 32, k, 128 * p);
      }
      {
        float ag[24], au[24];
        auto mma48 = [&](int, uint32_t a0, uint32_t a1, uint32_t a2, uint32_t a3, uint64_t d, bool acc) {
          wgmma_rs_n48(ag, a0, a1, a2, a3, d, acc);
          wgmma_rs_n48(au, a0, a1, a2, a3, d + 1024, acc);
        };
#pragma unroll
        for (int c = 0; c < 4; c++) {
          GU_TURN(0, mma48, c, 8 + c);
          if (c == 3) DN_VALIDATE(0);
          if (c > 0) {
#pragma unroll
            for (int e = 0; e < 8; e++) a[c - 1][e] = ld_try(hsrc + dn_step(c - 1, e) * 32);
          }
          FINE2(32 + c);
        }
        GU_END(ag, 11);
        pin(au);
#pragma unroll
        for (int k = 0; k < 3; k++)
          if (k == 0 || g != 7) HH_OUT(ag, au, k, 256);
      }
    }
    FINE2(36);
    {
      const uint4* src = hsrc;
      float keep[32], send[32];
      const uint32_t dd = db + ((8192 >> 4) << 16);
#pragma unroll
      for (int t = 0; t < 4; t++) {
        uint4* at = a[t % 3];
        const uint32_t d = dd + ring_slot(t) * (STAGE >> 4);
        mbar_wait(bar + 8 * (B_FULL + ring_slot(t)), 0);
        bar_sync(6 + wg, 256);
        wg_fence();
#pragma unroll
        for (int e = 0; e < 8; e++) {
          wgmma_rs_n64(keep, at[e].x, at[e].y, at[e].z, at[e].w, mkdesc(d + (e >> 2) * 1024 + (e & 3) * 128), (t | e) != 0);
          wgmma_rs_n64(send, at[e].x, at[e].y, at[e].z, at[e].w, mkdesc(d + 512 + (e >> 2) * 1024 + (e & 3) * 128), (t | e) != 0);
        }
        wg_commit();
        bar_arrive(7 - wg, 256);
        DN_VALIDATE(t + 1);
        wg_wait<1>();
        uint4* an = a[(t + 2) % 3];
        if (t == 0) {
#pragma unroll
          for (int e = 0; e < 4; e++) x1[e] = lds128(sb + OFF_RED + e * 4096 + tid * 16);
          arrive_both(bar + 8 * (B_EMPTY + 2), lane + (int)((x1[0].x ^ x1[1].x ^ x1[2].x ^ x1[3].x) == 0x12345u && tag == 0) * 32);
        } else if (t == 1) {
#pragma unroll
          for (int e = 0; e < 8; e++) an[e] = ld_try(src + dn_step(3, e) * 32);
        } else {
#pragma unroll
          for (int e = 0; e < 3; e++) {
            an[e] = ld_try(src + dn_step(t + 2, e) * 32);
            an[4 + e] = ld_try(src + dn_step(t + 2, 4 + e) * 32);
          }
        }
        FINE2(37 + t);
      }
      DN_VALIDATE(5);
      mbar_wait(bar + 8 * (B_FULL + ring_slot(4)), 0);
      mbar_wait(bar + 8 * (B_FULL + ring_slot(5)), 0);
      mbar_wait(bar + 8 * (B_EMPTY + 2), 1);
#define DN_TAIL(ACC, OFFS, T)                                                                                         \
  _Pragma("unroll") for (int e = 0; e < 7; e++)                                                                       \
    if (e != 3)                                                                                                       \
      wgmma_rs_n64(ACC, a[(T) % 3][e].x, a[(T) % 3][e].y, a[(T) % 3][e].z, a[(T) % 3][e].w,                           \
                   mkdesc(dd + ring_slot(T) * (STAGE >> 4) + (OFFS) + (e >> 2) * 1024 + (e & 3) * 128), true);
      wg_fence();
      DN_TAIL(send, 512, 4);
      DN_TAIL(send, 512, 5);
      wg_commit();
      wg_wait<0>();
      pin(send);

      FINE2(42);
      uint32_t rbar;
      asm volatile("mapa.shared::cluster.u32 %0, %1, %2;" : "=r"(rbar) : "r"(bar), "r"(rank ^ 1));
      const uint32_t roff = OFF_RED + warp * 4096 + lane * 16;
      const uint32_t rbuf = rbar - OFF_BAR + roff, rb = rbar + 8 * (B_RED + wg);
#pragma unroll
      for (int i = 0; i < 8; i++)
        asm volatile("st.async.weak.shared::cluster.mbarrier::complete_tx::bytes.v4.f32 [%0], {%1,%2,%3,%4}, [%5];" ::"r"(rbuf + i * 512),
                     "f"(send[4 * i]), "f"(send[4 * i + 1]), "f"(send[4 * i + 2]), "f"(send[4 * i + 3]), "r"(rb) : "memory");
      FINE2(43);
      wg_fence();
      DN_TAIL(keep, 0, 4);
      DN_TAIL(keep, 0, 5);
      wg_commit();
      wg_wait<0>();
      pin(keep);
      FINE2(44);
      mbar_wait_cluster(bar + 8 * (B_RED + wg), 0);
      FINE2(45);
      uint32_t ow[16];
#pragma unroll
      for (int t = 0; t < 8; t++) {
        const uint4 o = lds128(sb + roff + t * 512);
        const uint32_t gb = lds32(sb + OFF_TMP + (4 * t + q) * 16 + 12);
        const float gl = bf_lo(gb), gh = bf_hi(gb);
        const uint32_t xa = (t & 1) ? x1[t >> 1].z : x1[t >> 1].x, xb = (t & 1) ? x1[t >> 1].w : x1[t >> 1].y;
        ow[2 * t] = pack2(fmaf(gl, keep[4 * t] + __uint_as_float(o.x), bf_lo(xa)), fmaf(gh, keep[4 * t + 1] + __uint_as_float(o.y), bf_hi(xa)));
        ow[2 * t + 1] = pack2(fmaf(gl, keep[4 * t + 2] + __uint_as_float(o.z), bf_lo(xb)), fmaf(gh, keep[4 * t + 3] + __uint_as_float(o.w), bf_hi(xb)));
      }
      const uint32_t patch = sb + OFF_RED + warp * 4096;
      __syncwarp();
#pragma unroll
      for (int t = 0; t < 4; t++)
        stsm4(patch + (lane & 15) * 128 + (((2 * t + (lane >> 4)) ^ (lane & 7)) << 4), ow[4 * t], ow[4 * t + 1], ow[4 * t + 2], ow[4 * t + 3]);
      __syncwarp();
      __nv_bfloat16* op = gout + (size_t)(16 * rt + (lane >> 3)) * kD + 64 * gd + (lane & 7) * 8;
#pragma unroll
      for (int t = 0; t < 4; t++) {
        const int row = 4 * t + (lane >> 3);
        asm volatile("" ::: "memory");
        *reinterpret_cast<uint4*>(op + 4 * t * kD) = lds128(patch + row * 128 + (((lane & 7) ^ (row & 7)) << 4));
      }
      FINE2(46);
    }
  }
}

typedef CUresult (*EncodeFn)(CUtensorMap*, CUtensorMapDataType, cuuint32_t, void*, const cuuint64_t*, const cuuint64_t*, const cuuint32_t*,
                             const cuuint32_t*, CUtensorMapInterleave, CUtensorMapSwizzle, CUtensorMapL2promotion, CUtensorMapFloatOOBfill);

void encode(EncodeFn fn, CUtensorMap* tm, const void* base, int rank, const cuuint64_t* dims, const cuuint64_t* strides, const cuuint32_t* box) {
  const cuuint32_t es[5] = {1, 1, 1, 1, 1};
  CUresult rc = fn(tm, CU_TENSOR_MAP_DATA_TYPE_BFLOAT16, rank, const_cast<void*>(base), dims, strides, box, es, CU_TENSOR_MAP_INTERLEAVE_NONE,
                   CU_TENSOR_MAP_SWIZZLE_128B, CU_TENSOR_MAP_L2_PROMOTION_L2_128B, CU_TENSOR_MAP_FLOAT_OOB_FILL_NONE);
  (void)rc;
}

}

extern "C" void kernel_launch(void* const* d_in, const int* in_sizes, int n_in, void* d_out, int out_size) {
  (void)in_sizes; (void)n_in; (void)out_size;
  static EncodeFn fn = nullptr;
  static Scratch* scratch = nullptr;
  if (!fn) {
    void* p = nullptr;
    cudaDriverEntryPointQueryResult qr;
    cudaGetDriverEntryPoint("cuTensorMapEncodeTiled", &p, cudaEnableDefault, &qr);
    fn = (EncodeFn)p;
    cudaGetSymbolAddress((void**)&scratch, g_s);
    cudaFuncSetAttribute(fused_block_kernel, cudaFuncAttributeMaxDynamicSharedMemorySize, SMEM_BYTES);
  }
  Params P;
  const __nv_bfloat16* x = (const __nv_bfloat16*)d_in[0];
  const __nv_bfloat16* wqkv = (const __nv_bfloat16*)d_in[1];
  P.wo = (const __nv_bfloat16*)d_in[2];
  P.wg = (const __nv_bfloat16*)d_in[4];
  P.wu = (const __nv_bfloat16*)d_in[5];
  P.wd = (const __nv_bfloat16*)d_in[6];
  {
    const cuuint64_t dims[2] = {1536, 512};
    const cuuint64_t str[1] = {3072};
    const cuuint32_t box[2] = {64, 128};
    encode(fn, &P.tm_qkv, wqkv, 2, dims, str, box);
    const cuuint64_t dimx[2] = {512, 2048};
    const cuuint64_t strx[1] = {1024};
    encode(fn, &P.tm_x, x, 2, dimx, strx, box);
  }
  {
    const cuuint64_t dims[2] = {512, 512};
    const cuuint64_t str[1] = {1024};
    const cuuint32_t box[2] = {64, 256};
    encode(fn, &P.tm_wo, P.wo, 2, dims, str, box);
  }
  {
    const cuuint64_t dims0[3] = {176, 7, 512}, dims1[3] = {144, 1, 512};
    const cuuint64_t str[2] = {352, 2 * kF};
    const cuuint32_t box[3] = {64, 1, 128};
    encode(fn, &P.tm_g0, P.wg, 3, dims0, str, box);
    encode(fn, &P.tm_u0, P.wu, 3, dims0, str, box);
    encode(fn, &P.tm_g1, P.wg + 7 * 176, 3, dims1, str, box);
    encode(fn, &P.tm_u1, P.wu + 7 * 176, 3, dims1, str, box);
  }
  {
    const cuuint64_t dims[2] = {512, kF};
    const cuuint64_t str[1] = {1024};
    const cuuint32_t box[2] = {64, 64};
    encode(fn, &P.tm_wd, P.wd, 2, dims, str, box);
  }
  fused_block_kernel<<<kCtas, kThreads, SMEM_BYTES>>>(scratch, x, (const __nv_bfloat16*)d_in[8], (const __nv_bfloat16*)d_in[7], (__nv_bfloat16*)d_out, P);
}
```

```cpp
#include <cuda_runtime.h>
#include <cuda_bf16.h>
#include <cuda.h>
#include <stdint.h>

namespace {

constexpr int kD = 512, kF = 1376;
constexpr float kScale = 0.25f * 1.4426950408889634f;
constexpr int kThreads = 384;
constexpr int kCtas = 128;

constexpr uint32_t U = 8192;
constexpr uint32_t OFF_K = 0;
constexpr uint32_t OFF_V = 6 * U;
constexpr uint32_t OFF_WV = 12 * U;
constexpr uint32_t OFF_WQ = 20 * U;
constexpr uint32_t STAGE = 4 * U;
constexpr uint32_t OFF_RED = 2 * STAGE;
constexpr uint32_t OFF_MISC = 28 * U;
constexpr uint32_t OFF_BAR = OFF_MISC;
constexpr uint32_t OFF_TMP = OFF_MISC + 512;
constexpr uint32_t OFF_TAB = OFF_MISC + 1024;
constexpr uint32_t SMEM_BYTES = OFF_MISC + 3072;

enum {
  B_X = 0  , B_WKV = 2  ,
  B_WO = 8, B_XR = 9, B_RED = 10  , B_M1 = 12,
  B_TAB = 13,
  B_KRDY = 14, B_KN = 15, B_VN = 16,
  B_XFREE = 17,
  B_FULL = 18  ,
  B_EMPTY = 25  ,
  B_COUNT = 32
};
__host__ __device__ constexpr uint32_t kv_off(int c) { return c == 0 ? 4 * U : (c == 1 ? 0 : (c == 2 ? 6 * U : OFF_WV)); }
__host__ __device__ constexpr uint32_t kv_lbo(int c) { return c == 0 ? 6 * U : 2 * U; }

__host__ __device__ constexpr int ring_slot(int t) { return (0x431065 >> (4 * (t % 6))) & 7; }
__host__ __device__ constexpr int dn_step(int t, int e) { return 11 * (2 * (t & 1) + (e >> 2)) + 4 * (t >> 1) + (e & 3); }

struct Scratch {
  uint4 o[128 * 32 * 32];
  uint4 h2[128 * 32 * 32];
  uint4 hh[128 * 86 * 32];
  uint4 kv[kCtas * 2 * 1024];
  float mod1[8][1024];
  float mod2[8][2048];
  uint4 st2[8][2048];
  unsigned epoch[2 * kCtas * 32];
};
__device__ Scratch g_s;

struct Params {
  CUtensorMap tm_x, tm_qkv, tm_wo, tm_g0, tm_g1, tm_u0, tm_u1, tm_wd, tm_wd48;
  const __nv_bfloat16 *wo, *wg, *wu, *wd;
};

constexpr int kSpinLimit = 1 << 16;

__device__ __forceinline__ void mbar_init(uint32_t b, int cnt) { asm volatile("mbarrier.init.shared::cta.b64 [%0], %1;" ::"r"(b), "r"(cnt) : "memory"); }
__device__ __forceinline__ void mbar_expect(uint32_t b, uint32_t bytes) { asm volatile("mbarrier.arrive.expect_tx.shared::cta.b64 _, [%0], %1;" ::"r"(b), "r"(bytes) : "memory"); }
__device__ __forceinline__ void mbar_arrive(uint32_t b) { asm volatile("mbarrier.arrive.shared::cta.b64 _, [%0];" ::"r"(b) : "memory"); }
__device__ __forceinline__ void mbar_wait(uint32_t b, uint32_t ph) {
  asm volatile("{\n.reg .pred p;\n.reg .u32 n;\nmov.u32 n, 0;\n"
               "W: mbarrier.try_wait.parity.shared::cta.b64 p, [%0], %1;\n@p bra D;\n"
               "add.u32 n, n, 1;\nsetp.lt.u32 p, n, 65536;\n@p bra W;\nD:\n}" ::"r"(b), "r"(ph) : "memory");
}
__device__ __forceinline__ void mbar_wait_cluster(uint32_t b, uint32_t ph) {
  asm volatile("{\n.reg .pred p;\n.reg .u32 n;\nmov.u32 n, 0;\n"
               "W: mbarrier.try_wait.parity.acquire.cluster.shared::cta.b64 p, [%0], %1;\n@p bra D;\n"
               "add.u32 n, n, 1;\nsetp.lt.u32 p, n, 65536;\n@p bra W;\nD:\n}" ::"r"(b), "r"(ph) : "memory");
}
__device__ __forceinline__ void bar_sync(int id, int n) { asm volatile("bar.sync %0, %1;" ::"r"(id), "r"(n) : "memory"); }
__device__ __forceinline__ void bar_arrive(int id, int n) { asm volatile("bar.arrive %0, %1;" ::"r"(id), "r"(n) : "memory"); }
__device__ __forceinline__ unsigned next_tag(unsigned e) { unsigned t; asm volatile("add.u32 %0, %1, 1;" : "=r"(t) : "r"(e) : "memory"); return t; }
__device__ __forceinline__ void fence_async_smem() { asm volatile("fence.proxy.async.shared::cta;" ::: "memory"); }
__device__ __forceinline__ void tma2d(uint32_t dst, const CUtensorMap* tm, int c0, int c1, uint32_t bar) {
  asm volatile("cp.async.bulk.tensor.2d.shared::cluster.global.mbarrier::complete_tx::bytes [%0], [%1, {%3, %4}], [%2];"
               ::"r"(dst), "l"(tm), "r"(bar), "r"(c0), "r"(c1) : "memory");
}
__device__ __forceinline__ void tma2d_mc(uint32_t dst, const CUtensorMap* tm, int c0, int c1, uint32_t bar) {
  asm volatile("cp.async.bulk.tensor.2d.shared::cluster.global.mbarrier::complete_tx::bytes.multicast::cluster [%0], [%1, {%3, %4}], [%2], %5;"
               ::"r"(dst), "l"(tm), "r"(bar), "r"(c0), "r"(c1), "h"((uint16_t)3) : "memory");
}
__device__ __forceinline__ void tma3d_mc(uint32_t dst, const CUtensorMap* tm, int c0, int c1, int c2, uint32_t bar) {
  asm volatile("cp.async.bulk.tensor.3d.shared::cluster.global.mbarrier::complete_tx::bytes.multicast::cluster [%0], [%1, {%3, %4, %5}], [%2], %6;"
               ::"r"(dst), "l"(tm), "r"(bar), "r"(c0), "r"(c1), "r"(c2), "h"((uint16_t)3) : "memory");
}
__device__ __forceinline__ void l2_prefetch(const void* p, uint32_t bytes) { asm volatile("cp.async.bulk.prefetch.L2.global [%0], %1;" ::"l"(p), "r"(bytes) : "memory"); }
__device__ __forceinline__ uint4 ld_try(const uint4* p) {
  uint4 v;
  asm volatile("ld.global.v4.u32 {%0,%1,%2,%3}, [%4];" : "=r"(v.x), "=r"(v.y), "=r"(v.z), "=r"(v.w) : "l"(p) : "memory");
  return v;
}
__device__ __forceinline__ void st_tag(unsigned tag, uint4* p, uint4 v) {
  asm volatile("{\n.reg .b64 lo, hi;\n.reg .b128 v;\n.reg .b32 w;\nlop3.b32 w, %4, %5, 1, 0xD8;\n"
               "mov.b64 lo, {%1, %2};\nmov.b64 hi, {%3, w};\nmov.b128 v, {lo, hi};\nst.relaxed.gpu.global.b128 [%0], v;\n}"
               ::"l"(p), "r"(v.x), "r"(v.y), "r"(v.z), "r"(v.w), "r"(tag) : "memory");
}
__device__ __forceinline__ void st_tag_if(bool c, unsigned tag, uint4* p, uint4 v) {
  asm volatile("{\n.reg .pred p;\n.reg .b64 lo, hi;\n.reg .b128 v;\n.reg .b32 w;\nsetp.ne.u32 p, %6, 0;\nlop3.b32 w, %4, %5, 1, 0xD8;\n"
               "mov.b64 lo, {%1, %2};\nmov.b64 hi, {%3, w};\nmov.b128 v, {lo, hi};\n@p st.relaxed.gpu.global.b128 [%0], v;\n}"
               ::"l"(p), "r"(v.x), "r"(v.y), "r"(v.z), "r"(v.w), "r"(tag), "r"((uint32_t)c) : "memory");
}
__device__ __forceinline__ ulonglong2 ld_rlx2(const void* p) {
  ulonglong2 v;
  asm volatile("ld.relaxed.gpu.global.v2.b64 {%0,%1}, [%2];" : "=l"(v.x), "=l"(v.y) : "l"(p) : "memory");
  return v;
}
__device__ __forceinline__ void st_rlx2(void* p, unsigned long long a, unsigned long long b) {
  asm volatile("st.relaxed.gpu.global.v2.b64 [%0], {%1,%2};" ::"l"(p), "l"(a), "l"(b) : "memory");
}
__device__ __forceinline__ unsigned clock32() { unsigned c; asm volatile("mov.u32 %0, %%clock;" : "=r"(c)); return c; }
__device__ __forceinline__ uint4 ldg128(const void* p) {
  uint4 v;
  asm volatile("ld.global.nc.v4.u32 {%0,%1,%2,%3}, [%4];" : "=r"(v.x), "=r"(v.y), "=r"(v.z), "=r"(v.w) : "l"(p));
  return v;
}
__device__ __forceinline__ uint4 lds128(uint32_t a) {
  uint4 v;
  asm volatile("ld.shared.v4.u32 {%0,%1,%2,%3}, [%4];" : "=r"(v.x), "=r"(v.y), "=r"(v.z), "=r"(v.w) : "r"(a));
  return v;
}
__device__ __forceinline__ uint32_t lds32(uint32_t a) { uint32_t v; asm volatile("ld.shared.u32 %0, [%1];" : "=r"(v) : "r"(a)); return v; }
__device__ __forceinline__ void sts32(uint32_t a, uint32_t v) { asm volatile("st.shared.u32 [%0], %1;" ::"r"(a), "r"(v) : "memory"); }
__device__ __forceinline__ void sts128f(uint32_t a, float x, float y, float z, float w) {
  asm volatile("st.shared.v4.f32 [%0], {%1,%2,%3,%4};" ::"r"(a), "f"(x), "f"(y), "f"(z), "f"(w) : "memory");
}
__device__ __forceinline__ void ldsm4(uint32_t (&r)[4], uint32_t a) {
  asm volatile("ldmatrix.sync.aligned.m8n8.x4.shared.b16 {%0,%1,%2,%3}, [%4];" : "=r"(r[0]), "=r"(r[1]), "=r"(r[2]), "=r"(r[3]) : "r"(a));
}
__device__ __forceinline__ void ldsm4t(uint32_t (&r)[4], uint32_t a) {
  asm volatile("ldmatrix.sync.aligned.m8n8.x4.trans.shared.b16 {%0,%1,%2,%3}, [%4];" : "=r"(r[0]), "=r"(r[1]), "=r"(r[2]), "=r"(r[3]) : "r"(a));
}
__device__ __forceinline__ void stsm4(uint32_t a, uint32_t r0, uint32_t r1, uint32_t r2, uint32_t r3) {
  asm volatile("stmatrix.sync.aligned.m8n8.x4.shared.b16 [%0], {%1,%2,%3,%4};" ::"r"(a), "r"(r0), "r"(r1), "r"(r2), "r"(r3) : "memory");
}
__device__ __forceinline__ void mma16816(float* d, uint32_t a0, uint32_t a1, uint32_t a2, uint32_t a3, uint32_t b0, uint32_t b1) {
  asm("mma.sync.aligned.m16n8k16.row.col.f32.bf16.bf16.f32 {%0,%1,%2,%3}, {%4,%5,%6,%7}, {%8,%9}, {%0,%1,%2,%3};"
      : "+f"(d[0]), "+f"(d[1]), "+f"(d[2]), "+f"(d[3]) : "r"(a0), "r"(a1), "r"(a2), "r"(a3), "r"(b0), "r"(b1));
}
__device__ __forceinline__ void mma1688(float* d, uint32_t a0, uint32_t a1, uint32_t b0) {
  asm("mma.sync.aligned.m16n8k8.row.col.f32.bf16.bf16.f32 {%0,%1,%2,%3}, {%4,%5}, {%6}, {%0,%1,%2,%3};"
      : "+f"(d[0]), "+f"(d[1]), "+f"(d[2]), "+f"(d[3]) : "r"(a0), "r"(a1), "r"(b0));
}
__device__ __forceinline__ void mma16816_z(float* d, uint32_t a0, uint32_t a1, uint32_t a2, uint32_t a3, uint32_t b0, uint32_t b1) {
  asm("mma.sync.aligned.m16n8k16.row.col.f32.bf16.bf16.f32 {%0,%1,%2,%3}, {%4,%5,%6,%7}, {%8,%9}, {%10,%10,%10,%10};"
      : "=f"(d[0]), "=f"(d[1]), "=f"(d[2]), "=f"(d[3]) : "r"(a0), "r"(a1), "r"(a2), "r"(a3), "r"(b0), "r"(b1), "f"(0.f));
}
__device__ __forceinline__ uint32_t pack2(float lo, float hi) { uint32_t r; asm("cvt.rn.bf16x2.f32 %0, %1, %2;" : "=r"(r) : "f"(hi), "f"(lo)); return r; }
__device__ __forceinline__ float bf_lo(uint32_t w) { return __uint_as_float(w << 16); }
__device__ __forceinline__ float bf_hi(uint32_t w) { return __uint_as_float(w & 0xFFFF0000u); }
__device__ __forceinline__ float bf_round(float x) { return __bfloat162float(__float2bfloat16_rn(x)); }
__device__ __forceinline__ uint32_t hfma2(uint32_t a, uint32_t b, uint32_t c) { uint32_t r; asm("fma.rn.bf16x2 %0, %1, %2, %3;" : "=r"(r) : "r"(a), "r"(b), "r"(c)); return r; }
__device__ __forceinline__ float ex2(float x) { float y; asm("ex2.approx.ftz.f32 %0, %1;" : "=f"(y) : "f"(x)); return y; }
struct RowNorm { uint32_t hi, c; };
__device__ __forceinline__ RowNorm make_norm(float mean, float rstd) {
  RowNorm n;
  const float h = bf_round(rstd);
  n.hi = pack2(h, h);
  n.c = pack2(-mean * h, -mean * h);
  return n;
}
__device__ __forceinline__ uint32_t norm1(uint32_t w, const RowNorm& n) { return hfma2(w, n.hi, n.c); }
__device__ __forceinline__ uint64_t mkdesc(uint32_t lo) {
  uint64_t d;
  asm("mov.b64 %0, {%1, %2};" : "=l"(d) : "r"(lo), "r"(0x40000040u));
  return d;
}
__device__ __forceinline__ void wg_fence() { asm volatile("wgmma.fence.sync.aligned;" ::: "memory"); }
__device__ __forceinline__ void wg_commit() { asm volatile("wgmma.commit_group.sync.aligned;" ::: "memory"); }
template <int N> __device__ __forceinline__ void wg_wait() { asm volatile("wgmma.wait_group.sync.aligned %0;" ::"n"(N) : "memory"); }
template <int N> __device__ __forceinline__ void pin(float (&d)[N]) {
#pragma unroll
  for (int i = 0; i < N; i++) asm volatile("" : "+f"(d[i])::"memory");
}
__device__ __forceinline__ float silu_bf(float c) { return bf_round(__fdividef(c, 1.f + __expf(-c))); }

__device__ __forceinline__ void wgmma_rs_n48_z(float (&d)[24], uint32_t a0, uint32_t a1, uint32_t a2, uint32_t a3, uint64_t desc) {
  asm volatile(
    "wgmma.mma_async.sync.aligned.m64n48k16.f32.bf16.bf16 "
    "{%0, %1, %2, %3, %4, %5, %6, %7, %8, %9, %10, %11, %12, %13, %14, %15, "
    "%16, %17, %18, %19, %20, %21, %22, %23}, "
    "{%24, %25, %26, %27}, %28, 0, 1, 1, 1;"
    : "=f"(d[0]), "=f"(d[1]), "=f"(d[2]), "=f"(d[3]), "=f"(d[4]), "=f"(d[5]), "=f"(d[6]), "=f"(d[7]),
      "=f"(d[8]), "=f"(d[9]), "=f"(d[10]), "=f"(d[11]), "=f"(d[12]), "=f"(d[13]), "=f"(d[14]), "=f"(d[15]),
      "=f"(d[16]), "=f"(d[17]), "=f"(d[18]), "=f"(d[19]), "=f"(d[20]), "=f"(d[21]), "=f"(d[22]), "=f"(d[23])
    : "r"(a0), "r"(a1), "r"(a2), "r"(a3), "l"(desc));
}

__device__ __forceinline__ void wgmma_rs_n48_a(float (&d)[24], uint32_t a0, uint32_t a1, uint32_t a2, uint32_t a3, uint64_t desc) {
  asm volatile(
    "wgmma.mma_async.sync.aligned.m64n48k16.f32.bf16.bf16 "
    "{%0, %1, %2, %3, %4, %5, %6, %7, %8, %9, %10, %11, %12, %13, %14, %15, "
    "%16, %17, %18, %19, %20, %21, %22, %23}, "
    "{%24, %25, %26, %27}, %28, 1, 1, 1, 1;"
    : "+f"(d[0]), "+f"(d[1]), "+f"(d[2]), "+f"(d[3]), "+f"(d[4]), "+f"(d[5]), "+f"(d[6]), "+f"(d[7]),
      "+f"(d[8]), "+f"(d[9]), "+f"(d[10]), "+f"(d[11]), "+f"(d[12]), "+f"(d[13]), "+f"(d[14]), "+f"(d[15]),
      "+f"(d[16]), "+f"(d[17]), "+f"(d[18]), "+f"(d[19]), "+f"(d[20]), "+f"(d[21]), "+f"(d[22]), "+f"(d[23])
    : "r"(a0), "r"(a1), "r"(a2), "r"(a3), "l"(desc));
}

__device__ __forceinline__ void wgmma_rs_n48(float (&d)[24], uint32_t a0, uint32_t a1, uint32_t a2, uint32_t a3, uint64_t desc, bool acc) {
  if (acc) wgmma_rs_n48_a(d, a0, a1, a2, a3, desc); else wgmma_rs_n48_z(d, a0, a1, a2, a3, desc);
}

__device__ __forceinline__ void wgmma_rs_n64_z(float (&d)[32], uint32_t a0, uint32_t a1, uint32_t a2, uint32_t a3, uint64_t desc) {
  asm volatile(
    "wgmma.mma_async.sync.aligned.m64n64k16.f32.bf16.bf16 "
    "{%0, %1, %2, %3, %4, %5, %6, %7, %8, %9, %10, %11, %12, %13, %14, %15, "
    "%16, %17, %18, %19, %20, %21, %22, %23, %24, %25, %26, %27, %28, %29, %30, %31}, "
    "{%32, %33, %34, %35}, %36, 0, 1, 1, 1;"
    : "=f"(d[0]), "=f"(d[1]), "=f"(d[2]), "=f"(d[3]), "=f"(d[4]), "=f"(d[5]), "=f"(d[6]), "=f"(d[7]),
      "=f"(d[8]), "=f"(d[9]), "=f"(d[10]), "=f"(d[11]), "=f"(d[12]), "=f"(d[13]), "=f"(d[14]), "=f"(d[15]),
      "=f"(d[16]), "=f"(d[17]), "=f"(d[18]), "=f"(d[19]), "=f"(d[20]), "=f"(d[21]), "=f"(d[22]), "=f"(d[23]),
      "=f"(d[24]), "=f"(d[25]), "=f"(d[26]), "=f"(d[27]), "=f"(d[28]), "=f"(d[29]), "=f"(d[30]), "=f"(d[31])
    : "r"(a0), "r"(a1), "r"(a2), "r"(a3), "l"(desc));
}

__device__ __forceinline__ void wgmma_rs_n64_a(float (&d)[32], uint32_t a0, uint32_t a1, uint32_t a2, uint32_t a3, uint64_t desc) {
  asm volatile(
    "wgmma.mma_async.sync.aligned.m64n64k16.f32.bf16.bf16 "
    "{%0, %1, %2, %3, %4, %5, %6, %7, %8, %9, %10, %11, %12, %13, %14, %15, "
    "%16, %17, %18, %19, %20, %21, %22, %23, %24, %25, %26, %27, %28, %29, %30, %31}, "
    "{%32, %33, %34, %35}, %36, 1, 1, 1, 1;"
    : "+f"(d[0]), "+f"(d[1]), "+f"(d[2]), "+f"(d[3]), "+f"(d[4]), "+f"(d[5]), "+f"(d[6]), "+f"(d[7]),
      "+f"(d[8]), "+f"(d[9]), "+f"(d[10]), "+f"(d[11]), "+f"(d[12]), "+f"(d[13]), "+f"(d[14]), "+f"(d[15]),
      "+f"(d[16]), "+f"(d[17]), "+f"(d[18]), "+f"(d[19]), "+f"(d[20]), "+f"(d[21]), "+f"(d[22]), "+f"(d[23]),
      "+f"(d[24]), "+f"(d[25]), "+f"(d[26]), "+f"(d[27]), "+f"(d[28]), "+f"(d[29]), "+f"(d[30]), "+f"(d[31])
    : "r"(a0), "r"(a1), "r"(a2), "r"(a3), "l"(desc));
}

__device__ __forceinline__ void wgmma_rs_n64(float (&d)[32], uint32_t a0, uint32_t a1, uint32_t a2, uint32_t a3, uint64_t desc, bool acc) {
  if (acc) wgmma_rs_n64_a(d, a0, a1, a2, a3, desc); else wgmma_rs_n64_z(d, a0, a1, a2, a3, desc);
}

__device__ __forceinline__ void wgmma_rs_n128_z(float (&d)[64], uint32_t a0, uint32_t a1, uint32_t a2, uint32_t a3, uint64_t desc) {
  asm volatile(
    "wgmma.mma_async.sync.aligned.m64n128k16.f32.bf16.bf16 "
    "{%0, %1, %2, %3, %4, %5, %6, %7, %8, %9, %10, %11, %12, %13, %14, %15, "
    "%16, %17, %18, %19, %20, %21, %22, %23, %24, %25, %26, %27, %28, %29, %30, %31, "
    "%32, %33, %34, %35, %36, %37, %38, %39, %40, %41, %42, %43, %44, %45, %46, %47, "
    "%48, %49, %50, %51, %52, %53, %54, %55, %56, %57, %58, %59, %60, %61, %62, %63}, "
    "{%64, %65, %66, %67}, %68, 0, 1, 1, 1;"
    : "=f"(d[0]), "=f"(d[1]), "=f"(d[2]), "=f"(d[3]), "=f"(d[4]), "=f"(d[5]), "=f"(d[6]), "=f"(d[7]),
      "=f"(d[8]), "=f"(d[9]), "=f"(d[10]), "=f"(d[11]), "=f"(d[12]), "=f"(d[13]), "=f"(d[14]), "=f"(d[15]),
      "=f"(d[16]), "=f"(d[17]), "=f"(d[18]), "=f"(d[19]), "=f"(d[20]), "=f"(d[21]), "=f"(d[22]), "=f"(d[23]),
      "=f"(d[24]), "=f"(d[25]), "=f"(d[26]), "=f"(d[27]), "=f"(d[28]), "=f"(d[29]), "=f"(d[30]), "=f"(d[31]),
      "=f"(d[32]), "=f"(d[33]), "=f"(d[34]), "=f"(d[35]), "=f"(d[36]), "=f"(d[37]), "=f"(d[38]), "=f"(d[39]),
      "=f"(d[40]), "=f"(d[41]), "=f"(d[42]), "=f"(d[43]), "=f"(d[44]), "=f"(d[45]), "=f"(d[46]), "=f"(d[47]),
      "=f"(d[48]), "=f"(d[49]), "=f"(d[50]), "=f"(d[51]), "=f"(d[52]), "=f"(d[53]), "=f"(d[54]), "=f"(d[55]),
      "=f"(d[56]), "=f"(d[57]), "=f"(d[58]), "=f"(d[59]), "=f"(d[60]), "=f"(d[61]), "=f"(d[62]), "=f"(d[63])
    : "r"(a0), "r"(a1), "r"(a2), "r"(a3), "l"(desc));
}

__device__ __forceinline__ void wgmma_rs_n128_a(float (&d)[64], uint32_t a0, uint32_t a1, uint32_t a2, uint32_t a3, uint64_t desc) {
  asm volatile(
    "wgmma.mma_async.sync.aligned.m64n128k16.f32.bf16.bf16 "
    "{%0, %1, %2, %3, %4, %5, %6, %7, %8, %9, %10, %11, %12, %13, %14, %15, "
    "%16, %17, %18, %19, %20, %21, %22, %23, %24, %25, %26, %27, %28, %29, %30, %31, "
    "%32, %33, %34, %35, %36, %37, %38, %39, %40, %41, %42, %43, %44, %45, %46, %47, "
    "%48, %49, %50, %51, %52, %53, %54, %55, %56, %57, %58, %59, %60, %61, %62, %63}, "
    "{%64, %65, %66, %67}, %68, 1, 1, 1, 1;"
    : "+f"(d[0]), "+f"(d[1]), "+f"(d[2]), "+f"(d[3]), "+f"(d[4]), "+f"(d[5]), "+f"(d[6]), "+f"(d[7]),
      "+f"(d[8]), "+f"(d[9]), "+f"(d[10]), "+f"(d[11]), "+f"(d[12]), "+f"(d[13]), "+f"(d[14]), "+f"(d[15]),
      "+f"(d[16]), "+f"(d[17]), "+f"(d[18]), "+f"(d[19]), "+f"(d[20]), "+f"(d[21]), "+f"(d[22]), "+f"(d[23]),
      "+f"(d[24]), "+f"(d[25]), "+f"(d[26]), "+f"(d[27]), "+f"(d[28]), "+f"(d[29]), "+f"(d[30]), "+f"(d[31]),
      "+f"(d[32]), "+f"(d[33]), "+f"(d[34]), "+f"(d[35]), "+f"(d[36]), "+f"(d[37]), "+f"(d[38]), "+f"(d[39]),
      "+f"(d[40]), "+f"(d[41]), "+f"(d[42]), "+f"(d[43]), "+f"(d[44]), "+f"(d[45]), "+f"(d[46]), "+f"(d[47]),
      "+f"(d[48]), "+f"(d[49]), "+f"(d[50]), "+f"(d[51]), "+f"(d[52]), "+f"(d[53]), "+f"(d[54]), "+f"(d[55]),
      "+f"(d[56]), "+f"(d[57]), "+f"(d[58]), "+f"(d[59]), "+f"(d[60]), "+f"(d[61]), "+f"(d[62]), "+f"(d[63])
    : "r"(a0), "r"(a1), "r"(a2), "r"(a3), "l"(desc));
}

__device__ __forceinline__ void wgmma_rs_n128(float (&d)[64], uint32_t a0, uint32_t a1, uint32_t a2, uint32_t a3, uint64_t desc, bool acc) {
  if (acc) wgmma_rs_n128_a(d, a0, a1, a2, a3, desc); else wgmma_rs_n128_z(d, a0, a1, a2, a3, desc);
}


__device__ __forceinline__ void arrive_both(uint32_t b, int lane) {
  asm volatile("{\n.reg .pred p;\n.reg .u32 a;\nsetp.lt.u32 p, %1, 2;\n@p mapa.shared::cluster.u32 a, %0, %1;\n"
               "@p mbarrier.arrive.shared::cluster.b64 _, [a];\n}" ::"r"(b), "r"(lane) : "memory");
}
template <int N, int STRIDE> struct Val;
template <int STRIDE> struct Val<3, STRIDE> {
  static __device__ __forceinline__ void run(uint4* a, const uint4* p, unsigned par) {
    asm volatile(
      "{\n"
      ".reg .pred p, q;\n"
      ".reg .u32 n, t, m;\n"
      "mov.u32 n, 0;\n"
      "V:\n"
      "xor.b32 %3, %3, %14;\n"
      "xor.b32 %7, %7, %14;\n"
      "xor.b32 %11, %11, %14;\n"
      "mov.b32 m, %3;\n"
      "or.b32 m, m, %7;\n"
      "or.b32 m, m, %11;\n"
      "and.b32 m, m, 1;\n"
      "setp.ne.u32 p, m, 0;\n"
      "vote.sync.any.pred p, p, 0xffffffff;\n"
      "@!p bra E;\n"
      "add.u32 n, n, 1;\n"
      "and.b32 t, %3, 1;\n"
      "setp.ne.u32 q, t, 0;\n"
      "xor.b32 %3, %3, %14;\n"
      "@q ld.relaxed.gpu.global.v4.u32 {%0, %1, %2, %3}, [%12+0*%13];\n"
      "and.b32 t, %7, 1;\n"
      "setp.ne.u32 q, t, 0;\n"
      "xor.b32 %7, %7, %14;\n"
      "@q ld.relaxed.gpu.global.v4.u32 {%4, %5, %6, %7}, [%12+1*%13];\n"
      "and.b32 t, %11, 1;\n"
      "setp.ne.u32 q, t, 0;\n"
      "xor.b32 %11, %11, %14;\n"
      "@q ld.relaxed.gpu.global.v4.u32 {%8, %9, %10, %11}, [%12+2*%13];\n"
      "setp.lt.u32 p, n, 65536;\n"
      "@p bra V;\n"
      "E:\n"
      "}\n"
      : "+r"(a[0].x), "+r"(a[0].y), "+r"(a[0].z), "+r"(a[0].w), "+r"(a[1].x), "+r"(a[1].y), "+r"(a[1].z), "+r"(a[1].w), "+r"(a[2].x), "+r"(a[2].y), "+r"(a[2].z), "+r"(a[2].w)
      : "l"(p), "n"(STRIDE * 16), "r"(par) : "memory");
  }
};

template <int STRIDE> struct Val<4, STRIDE> {
  static __device__ __forceinline__ void run(uint4* a, const uint4* p, unsigned par) {
    asm volatile(
      "{\n"
      ".reg .pred p, q;\n"
      ".reg .u32 n, t, m;\n"
      "mov.u32 n, 0;\n"
      "V:\n"
      "xor.b32 %3, %3, %18;\n"
      "xor.b32 %7, %7, %18;\n"
      "xor.b32 %11, %11, %18;\n"
      "xor.b32 %15, %15, %18;\n"
      "mov.b32 m, %3;\n"
      "or.b32 m, m, %7;\n"
      "or.b32 m, m, %11;\n"
      "or.b32 m, m, %15;\n"
      "and.b32 m, m, 1;\n"
      "setp.ne.u32 p, m, 0;\n"
      "vote.sync.any.pred p, p, 0xffffffff;\n"
      "@!p bra E;\n"
      "add.u32 n, n, 1;\n"
      "and.b32 t, %3, 1;\n"
      "setp.ne.u32 q, t, 0;\n"
      "xor.b32 %3, %3, %18;\n"
      "@q ld.relaxed.gpu.global.v4.u32 {%0, %1, %2, %3}, [%16+0*%17];\n"
      "and.b32 t, %7, 1;\n"
      "setp.ne.u32 q, t, 0;\n"
      "xor.b32 %7, %7, %18;\n"
      "@q ld.relaxed.gpu.global.v4.u32 {%4, %5, %6, %7}, [%16+1*%17];\n"
      "and.b32 t, %11, 1;\n"
      "setp.ne.u32 q, t, 0;\n"
      "xor.b32 %11, %11, %18;\n"
      "@q ld.relaxed.gpu.global.v4.u32 {%8, %9, %10, %11}, [%16+2*%17];\n"
      "and.b32 t, %15, 1;\n"
      "setp.ne.u32 q, t, 0;\n"
      "xor.b32 %15, %15, %18;\n"
      "@q ld.relaxed.gpu.global.v4.u32 {%12, %13, %14, %15}, [%16+3*%17];\n"
      "setp.lt.u32 p, n, 65536;\n"
      "@p bra V;\n"
      "E:\n"
      "}\n"
      : "+r"(a[0].x), "+r"(a[0].y), "+r"(a[0].z), "+r"(a[0].w), "+r"(a[1].x), "+r"(a[1].y), "+r"(a[1].z), "+r"(a[1].w), "+r"(a[2].x), "+r"(a[2].y), "+r"(a[2].z), "+r"(a[2].w), "+r"(a[3].x), "+r"(a[3].y), "+r"(a[3].z), "+r"(a[3].w)
      : "l"(p), "n"(STRIDE * 16), "r"(par) : "memory");
  }
};

template <int STRIDE> struct Val<8, STRIDE> {
  static __device__ __forceinline__ void run(uint4* a, const uint4* p, unsigned par) {
    asm volatile(
      "{\n"
      ".reg .pred p, q;\n"
      ".reg .u32 n, t, m;\n"
      "mov.u32 n, 0;\n"
      "V:\n"
      "xor.b32 %3, %3, %34;\n"
      "xor.b32 %7, %7, %34;\n"
      "xor.b32 %11, %11, %34;\n"
      "xor.b32 %15, %15, %34;\n"
      "xor.b32 %19, %19, %34;\n"
      "xor.b32 %23, %23, %34;\n"
      "xor.b32 %27, %27, %34;\n"
      "xor.b32 %31, %31, %34;\n"
      "mov.b32 m, %3;\n"
      "or.b32 m, m, %7;\n"
      "or.b32 m, m, %11;\n"
      "or.b32 m, m, %15;\n"
      "or.b32 m, m, %19;\n"
      "or.b32 m, m, %23;\n"
      "or.b32 m, m, %27;\n"
      "or.b32 m, m, %31;\n"
      "and.b32 m, m, 1;\n"
      "setp.ne.u32 p, m, 0;\n"
      "vote.sync.any.pred p, p, 0xffffffff;\n"
      "@!p bra E;\n"
      "add.u32 n, n, 1;\n"
      "and.b32 t, %3, 1;\n"
      "setp.ne.u32 q, t, 0;\n"
      "xor.b32 %3, %3, %34;\n"
      "@q ld.relaxed.gpu.global.v4.u32 {%0, %1, %2, %3}, [%32+0*%33];\n"
      "and.b32 t, %7, 1;\n"
      "setp.ne.u32 q, t, 0;\n"
      "xor.b32 %7, %7, %34;\n"
      "@q ld.relaxed.gpu.global.v4.u32 {%4, %5, %6, %7}, [%32+1*%33];\n"
      "and.b32 t, %11, 1;\n"
      "setp.ne.u32 q, t, 0;\n"
      "xor.b32 %11, %11, %34;\n"
      "@q ld.relaxed.gpu.global.v4.u32 {%8, %9, %10, %11}, [%32+2*%33];\n"
      "and.b32 t, %15, 1;\n"
      "setp.ne.u32 q, t, 0;\n"
      "xor.b32 %15, %15, %34;\n"
      "@q ld.relaxed.gpu.global.v4.u32 {%12, %13, %14, %15}, [%32+3*%33];\n"
      "and.b32 t, %19, 1;\n"
      "setp.ne.u32 q, t, 0;\n"
      "xor.b32 %19, %19, %34;\n"
      "@q ld.relaxed.gpu.global.v4.u32 {%16, %17, %18, %19}, [%32+4*%33];\n"
      "and.b32 t, %23, 1;\n"
      "setp.ne.u32 q, t, 0;\n"
      "xor.b32 %23, %23, %34;\n"
      "@q ld.relaxed.gpu.global.v4.u32 {%20, %21, %22, %23}, [%32+5*%33];\n"
      "and.b32 t, %27, 1;\n"
      "setp.ne.u32 q, t, 0;\n"
      "xor.b32 %27, %27, %34;\n"
      "@q ld.relaxed.gpu.global.v4.u32 {%24, %25, %26, %27}, [%32+6*%33];\n"
      "and.b32 t, %31, 1;\n"
      "setp.ne.u32 q, t, 0;\n"
      "xor.b32 %31, %31, %34;\n"
      "@q ld.relaxed.gpu.global.v4.u32 {%28, %29, %30, %31}, [%32+7*%33];\n"
      "setp.lt.u32 p, n, 65536;\n"
      "@p bra V;\n"
      "E:\n"
      "}\n"
      : "+r"(a[0].x), "+r"(a[0].y), "+r"(a[0].z), "+r"(a[0].w), "+r"(a[1].x), "+r"(a[1].y), "+r"(a[1].z), "+r"(a[1].w), "+r"(a[2].x), "+r"(a[2].y), "+r"(a[2].z), "+r"(a[2].w), "+r"(a[3].x), "+r"(a[3].y), "+r"(a[3].z), "+r"(a[3].w), "+r"(a[4].x), "+r"(a[4].y), "+r"(a[4].z), "+r"(a[4].w), "+r"(a[5].x), "+r"(a[5].y), "+r"(a[5].z), "+r"(a[5].w), "+r"(a[6].x), "+r"(a[6].y), "+r"(a[6].z), "+r"(a[6].w), "+r"(a[7].x), "+r"(a[7].y), "+r"(a[7].z), "+r"(a[7].w)
      : "l"(p), "n"(STRIDE * 16), "r"(par) : "memory");
  }
};

template <int N, int STRIDE> __device__ __forceinline__ void validate(uint4* a, const uint4* p, unsigned tag) { Val<N, STRIDE>::run(a, p, tag & 1); }


__device__ __forceinline__ int fi(float x) { return __float_as_int(x); }

__device__ __forceinline__ uint32_t hadd2(uint32_t a, uint32_t b) { uint32_t r; asm("add.rn.bf16x2 %0, %1, %2;" : "=r"(r) : "r"(a), "r"(b)); return r; }
__device__ __forceinline__ uint32_t packt(float lo, float hi) { return __byte_perm(__float_as_uint(lo), __float_as_uint(hi), 0x7632); }
__device__ __forceinline__ void mma16816_c(float* d, const uint32_t* a, uint32_t b0, uint32_t b1, const float* c) {
  asm("mma.sync.aligned.m16n8k16.row.col.f32.bf16.bf16.f32 {%0,%1,%2,%3}, {%4,%5,%6,%7}, {%8,%9}, {%10,%11,%12,%13};"
      : "=f"(d[0]), "=f"(d[1]), "=f"(d[2]), "=f"(d[3])
      : "r"(a[0]), "r"(a[1]), "r"(a[2]), "r"(a[3]), "r"(b0), "r"(b1), "f"(c[0]), "f"(c[1]), "f"(c[2]), "f"(c[3]));
}
__device__ __forceinline__ void qk_block(float* s, const uint32_t* qf, uint32_t addr, const float* c) {
  uint32_t kf[4];
  ldsm4(kf, addr);
  mma16816_c(s, qf, kf[0], kf[1], c);
  mma16816_c(s + 4, qf, kf[2], kf[3], c);
}
__device__ __forceinline__ void qk_edge(float* s, const uint32_t* qf, uint32_t kaddr, bool p0, bool p1) {
  float d[8];
  const float z[4] = {};
  qk_block(s, qf, kaddr, z);
  qk_block(d, qf, kaddr + 16 * 2048, z);
  s[0] = p0 ? s[0] : d[0];
  s[1] = p1 ? s[1] : d[1];
  s[2] = d[2];
  s[3] = d[3];
  s[6] = p0 ? s[6] : d[6];
  s[7] = p1 ? s[7] : d[7];
}
__device__ __forceinline__ void max_block(float& m0, float& m1, const float* s) {
  m0 = fmaxf(fmaxf(m0, s[0]), fmaxf(s[1], fmaxf(s[4], s[5])));
  m1 = fmaxf(fmaxf(m1, s[2]), fmaxf(s[3], fmaxf(s[6], s[7])));
}
__device__ __forceinline__ void edge_offset(float* e, float m0, float m1, float& n0, float& n1) {
  max_block(m0, m1, e);
  m0 = fmaxf(m0, __shfl_xor_sync(0xffffffffu, m0, 1)); m1 = fmaxf(m1, __shfl_xor_sync(0xffffffffu, m1, 1));
  m0 = fmaxf(m0, __shfl_xor_sync(0xffffffffu, m0, 2)); m1 = fmaxf(m1, __shfl_xor_sync(0xffffffffu, m1, 2));
  n0 = -m0; n1 = -m1;
#pragma unroll
  for (int k = 0; k < 8; k++) e[k] += (k & 2) ? n1 : n0;
}
__device__ __forceinline__ void exp_block(uint32_t* pa, const float* s) {
#pragma unroll
  for (int k = 0; k < 4; k++) pa[k] = packt(ex2(s[2 * k]), ex2(s[2 * k + 1]));
}
__device__ __forceinline__ void pv_edge(float* o0, float* o1, const uint32_t* pa, uint32_t va, uint32_t msk) {
  uint32_t vf[4];
  ldsm4t(vf, va);
  mma16816_z(o0, pa[0] & msk, 0u, pa[2], pa[3] & msk, vf[0], vf[1]);
  mma16816_z(o1, pa[0] & msk, 0u, pa[2], pa[3] & msk, vf[2], vf[3]);
  ldsm4t(vf, va + 16 * 2048);
  mma16816(o0, pa[0] & ~msk, pa[1], 0u, pa[3] & ~msk, vf[0], vf[1]);
  mma16816(o1, pa[0] & ~msk, pa[1], 0u, pa[3] & ~msk, vf[2], vf[3]);
}
__device__ __forceinline__ void pv_block(float* o0, float* o1, const uint32_t* pa, uint32_t va) {
  uint32_t vf[4];
  ldsm4t(vf, va);
  mma16816(o0, pa[0], pa[1], pa[2], pa[3], vf[0], vf[1]);
  mma16816(o1, pa[0], pa[1], pa[2], pa[3], vf[2], vf[3]);
}
__device__ __forceinline__ uint4 attn_out(const float* o0, const float* o1, const float* l) {
  float i0, i1;
  asm("rcp.approx.ftz.f32 %0, %1;" : "=f"(i0) : "f"(l[0]));
  asm("rcp.approx.ftz.f32 %0, %1;" : "=f"(i1) : "f"(l[2]));
  return make_uint4(pack2(o0[0] * i0, o0[1] * i0), pack2(o0[2] * i1, o0[3] * i1), pack2(o1[0] * i0, o1[1] * i0), pack2(o1[2] * i1, o1[3] * i1));
}

__device__ __forceinline__ bool tag_ok(const ulonglong2& a, unsigned tag) { return (unsigned)(a.x >> 32) == tag && (unsigned)(a.y >> 32) == tag; }
__device__ __forceinline__ float lo_f(unsigned long long v) { return __uint_as_float((unsigned)v); }

template <bool V> struct BoolC { static constexpr bool value = V; };

__global__ void __cluster_dims__(2, 1, 1) __launch_bounds__(kThreads, 1)
fused_block_kernel(Scratch* __restrict__ S, const __nv_bfloat16* __restrict__ gx, const __nv_bfloat16* __restrict__ gwmod,
                   const __nv_bfloat16* __restrict__ gc, __nv_bfloat16* __restrict__ gout, const __grid_constant__ Params P) {
  extern __shared__ __align__(1024) uint8_t smem[];
  const uint32_t sb = (uint32_t)__cvta_generic_to_shared(smem);
  const int tid = threadIdx.x, lane = tid & 31;
  const int warp = __shfl_sync(0xffffffffu, tid >> 5, 0);
  const int rank = blockIdx.x & 1;
  int R, g;
  {
    const int t = (int)(blockIdx.x >> 1) - 4;
    if (t < 0) { R = 0; g = 8 + t; }
    else if (t < 32) { R = t & 7; g = t >> 3; }
    else { R = 1 + (t - 32) % 7; g = 4 + (t - 32) / 7; }
  }
  const int r = 2 * R + rank, cta = 8 * r + g;
  const int rd = 2 * R + (g >> 2), gd = 2 * (g & 3) + rank;
  const uint32_t bar = sb + OFF_BAR;

  if (warp >= 8) {
    asm volatile("setmaxnreg.dec.sync.aligned.u32 40;");
    const int aw = warp - 8;
    uint4 wm[4];
    const int au = 32 * aw + lane;
#pragma unroll
    for (int i = 0; i < 4; i++) wm[i] = ldg128(gwmod + (size_t)(64 * g + (au >> 3) + 16 * i) * 3072 + 64 * r + 8 * (au & 7));
    const float cv = __bfloat162float(gc[64 * g + (au >> 3) + 16 * (au & 3)]);
    const unsigned epoch = S->epoch[cta * 32 + lane];
    asm volatile("barrier.cluster.arrive.relaxed.aligned;" ::: "memory");
    {
      const float sv = silu_bf(cv);
      float v[8] = {};
#pragma unroll
      for (int i = 0; i < 4; i++) {
        const float sc = __shfl_sync(0xffffffffu, sv, (lane & 24) + i);
        const uint32_t* a = reinterpret_cast<const uint32_t*>(&wm[i]);
#pragma unroll
        for (int k = 0; k < 4; k++) { v[2 * k] = fmaf(sc, bf_lo(a[k]), v[2 * k]); v[2 * k + 1] = fmaf(sc, bf_hi(a[k]), v[2 * k + 1]); }
      }
      bool up = lane & 16;
#pragma unroll
      for (int i = 0; i < 4; i++) { const float snd = up ? v[i] : v[i + 4], kp = up ? v[i + 4] : v[i]; v[i] = kp + __shfl_xor_sync(0xffffffffu, snd, 16); }
      up = lane & 8;
#pragma unroll
      for (int i = 0; i < 2; i++) { const float snd = up ? v[i] : v[i + 2], kp = up ? v[i + 2] : v[i]; v[i] = kp + __shfl_xor_sync(0xffffffffu, snd, 8); }
      const int col = 8 * (lane & 7) + 2 * (lane >> 3);
      sts32(sb + OFF_TAB + (aw * 64 + col) * 4, __float_as_uint(v[0]));
      sts32(sb + OFF_TAB + (aw * 64 + col + 1) * 4, __float_as_uint(v[1]));
    }
    bar_sync(2, 128);
    const unsigned tag = next_tag(epoch);
    if (aw == 1 && lane < 16) {
      float t0 = 0.f, t1 = 0.f, t2 = 0.f, t3 = 0.f;
#pragma unroll
      for (int i = 0; i < 4; i++) {
        const uint4 p = lds128(sb + OFF_TAB + i * 256 + lane * 16);
        t0 += __uint_as_float(p.x); t1 += __uint_as_float(p.y); t2 += __uint_as_float(p.z); t3 += __uint_as_float(p.w);
      }
      st_tag(tag, reinterpret_cast<uint4*>(&S->mod1[g][64 * r + 4 * lane]),
             make_uint4(__float_as_uint(t0), __float_as_uint(t1), __float_as_uint(t2), __float_as_uint(t3)));
    }
    bar_sync(4, 384);
    if (aw == 1 && lane == 0) mbar_arrive(bar + 8 * B_M1);
    if (aw == 3) S->epoch[cta * 32 + lane] = tag;
    if (aw == 1) {
      if (lane < 2) mbar_expect(bar + 8 * (B_RED + lane), 16384);
      mbar_wait(bar + 8 * B_VN, 0);
      if (lane < 3) l2_prefetch(reinterpret_cast<const uint8_t*>((&P.wg)[lane]) + cta * 11008, 11008);
    } else if (aw == 2) {
      if (lane < 3) mbar_expect(bar + 8 * (B_WKV + 3 + lane), 32768);
      mbar_wait(bar + 8 * B_XFREE, 0);
      if (lane == 0) tma2d_mc(sb + kv_off(3) + rank * kv_lbo(3), &P.tm_qkv, 512 + 512 * rank + 64 * g, 384, bar + 8 * (B_WKV + 3));
      else if (lane < 3) {
        const int i = 2 * (lane - 1) + rank;
        tma2d_mc(sb + OFF_WQ + i * 2 * U, &P.tm_qkv, 64 * g, 128 * i, bar + 8 * (B_WKV + 3 + lane));
      }
      if (lane == 4) l2_prefetch(reinterpret_cast<const uint8_t*>(P.wo) + cta * 4096, 4096);
    } else {
      const int u = (aw == 0 ? 0 : 32) + lane;
      mbar_wait(bar + 8 * B_XFREE, 0);
      const __nv_bfloat16* wp = gwmod + (size_t)(64 * g + (u >> 4)) * 3072 + 1024 + 128 * r + 8 * (u & 15);
      const float sv = silu_bf(__bfloat162float(gc[64 * g + (u >> 4) + 4 * (u & 15)]));
      float acc[8];
#pragma unroll
      for (int i = 0; i < 8; i++) acc[i] = 0.f;
#pragma unroll 1
      for (int bt = 0; bt < 4; bt++) {
        uint4 w[4];
#pragma unroll
        for (int i = 0; i < 4; i++) w[i] = ldg128(wp + (size_t)(bt * 4 + i) * 4 * 3072);
        if (bt == 0) {
#pragma unroll
          for (int i = 4; i < 16; i++) asm volatile("prefetch.global.L1 [%0];" ::"l"(wp + (size_t)i * 4 * 3072));
        }
#pragma unroll
        for (int i = 0; i < 4; i++) {
          const float s = __shfl_sync(0xffffffffu, sv, (lane & 16) + bt * 4 + i);
          const uint32_t* ww = reinterpret_cast<const uint32_t*>(&w[i]);
#pragma unroll
          for (int k = 0; k < 4; k++) {
            acc[2 * k] = fmaf(s, bf_lo(ww[k]), acc[2 * k]);
            acc[2 * k + 1] = fmaf(s, bf_hi(ww[k]), acc[2 * k + 1]);
          }
        }
      }
#pragma unroll
      for (int i = 0; i < 8; i++) acc[i] += __shfl_xor_sync(0xffffffffu, acc[i], 16);
      const int hf = lane >> 4;
      float4 v = hf ? make_float4(acc[4], acc[5], acc[6], acc[7]) : make_float4(acc[0], acc[1], acc[2], acc[3]);
      if (aw == 3) sts128f(sb + OFF_TMP + lane * 16, v.x, v.y, v.z, v.w);
      bar_sync(3, 64);
      if (aw == 0) {
        const uint4 o = lds128(sb + OFF_TMP + lane * 16);
        st_tag(tag, reinterpret_cast<uint4*>(&S->mod2[g][128 * r + 8 * (lane & 15) + 4 * hf]),
               make_uint4((__float_as_uint(v.x + __uint_as_float(o.x))), (__float_as_uint(v.y + __uint_as_float(o.y))),
                          (__float_as_uint(v.z + __uint_as_float(o.z))), (__float_as_uint(v.w + __uint_as_float(o.w)))));
      }
    }
    __syncwarp();
    mbar_wait(bar + 8 * B_VN, 0);
    if (aw == 0 && lane == 0) {
      mbar_expect(bar + 8 * B_WO, 65536);
      tma2d(sb + OFF_WV, &P.tm_wo, 64 * gd, 0, bar + 8 * B_WO);
      tma2d(sb + OFF_WV + 4 * U, &P.tm_wo, 64 * gd, 256, bar + 8 * B_WO);
    }
    bar_sync(2, 128);
    {
      const int col = 512 * aw + 64 * gd + 4 * (lane & 15);
      const uint4* mp = reinterpret_cast<const uint4*>(&S->mod2[0][col]);
      float v0 = 0.f, v1 = 0.f, v2 = 0.f, v3 = 0.f;
#pragma unroll 1
      for (int pb = 0; pb < 8; pb += 4) {
        uint4 a[4];
#pragma unroll
        for (int k = 0; k < 4; k++) a[k] = ld_try(mp + (pb + k) * 512);
        validate<4, 512>(a, mp + pb * 512, tag);
#pragma unroll
        for (int k = 0; k < 4; k++) {
          v0 += __uint_as_float(a[k].x); v1 += __uint_as_float(a[k].y); v2 += __uint_as_float(a[k].z); v3 += __uint_as_float(a[k].w);
        }
      }
      const float add = aw == 2 ? 1.f : 0.f;
      sts32(sb + OFF_TMP + 32 * (lane & 15) + 4 * aw, pack2(add + bf_round(v0), add + bf_round(v1)));
      sts32(sb + OFF_TMP + 32 * (lane & 15) + 16 + 4 * aw, pack2(add + bf_round(v2), add + bf_round(v3)));
      __syncwarp();
      if (lane == 0) mbar_arrive(bar + 8 * B_TAB);
    }
    asm volatile("barrier.cluster.wait.aligned;" ::: "memory");
    if (aw == 0) {
      const CUtensorMap* tgu = (&P.tm_g0) + (g == 7 ? 1 : 0) + 2 * rank;
      const int sl = g == 7 ? 0 : g;
#pragma unroll 1
      for (int t = 0; t < 18; t++) {
        const int slot = ring_slot(t);
        mbar_wait(bar + 8 * (B_EMPTY + slot), (t / 6) & 1);
        if (t >= 2) mbar_wait(bar + 8 * (B_FULL + ring_slot(t - 2)), ((t - 2) / 6) & 1);
        const uint32_t dst = sb + slot * STAGE, fb = bar + 8 * (B_FULL + slot);
        if (lane == 0) mbar_expect(fb, t < 16 ? 32768 : 24576);
        __syncwarp();
        if (t < 12) {
          if (lane == 0) tma3d_mc(dst + rank * 16384, tgu, 64 * (t >> 2), sl, 128 * (t & 3), fb);
        } else if (lane < 4) {
          const int ch = 2 * (t - 12) + (lane >> 1);
          const int row = 704 * rank + 176 * (ch & 3) + 64 * (ch >> 2);
          tma2d(dst + lane * 8192, t < 16 ? &P.tm_wd : &P.tm_wd48, 128 * (g & 3) + 64 * ((lane & 1) ^ rank), row, fb);
        }
      }
    } else if (aw == 1 && lane == 0) {
      mbar_wait(bar + 8 * B_KRDY, 1);
      mbar_expect(bar + 8 * B_XR, 16384);
      tma2d(sb + OFF_RED + 2 * U, &P.tm_x, 64 * gd, 128 * rd, bar + 8 * B_XR);
    }
  } else {
    asm volatile("setmaxnreg.inc.sync.aligned.u32 232;");
    const int wg = warp >> 2, gq = lane >> 2, q = lane & 3;
    const uint32_t db = (sb & 0x3FFFF) >> 4;
    uint32_t qf[16];
    unsigned tag;
    {
      if (lane == 0) {
        if (warp == 0) {
          asm volatile("prefetch.tensormap [%0];" ::"l"(&P.tm_x) : "memory");
          asm volatile("prefetch.tensormap [%0];" ::"l"(&P.tm_qkv) : "memory");
#pragma unroll
          for (int i = B_X; i < B_WKV + 3; i++) mbar_init(bar + 8 * i, 1);
          fence_async_smem();
#pragma unroll
          for (int c = 0; c < 8; c++) {
            if (!(c & 3)) mbar_expect(bar + 8 * (B_X + (c >> 2)), 65536);
            tma2d(sb + OFF_WV + c * 2 * U, &P.tm_x, 64 * c, 128 * r, bar + 8 * (B_X + (c >> 2)));
          }
#pragma unroll
          for (int c = 0; c < 3; c++) {
            mbar_expect(bar + 8 * (B_WKV + c), 32768);
            tma2d(sb + kv_off(c), &P.tm_qkv, 512 + 64 * g, 128 * c, bar + 8 * (B_WKV + c));
            tma2d(sb + kv_off(c) + kv_lbo(c), &P.tm_qkv, 1024 + 64 * g, 128 * c, bar + 8 * (B_WKV + c));
          }
        } else if (warp == 1) {
#pragma unroll
          for (int i = B_WKV + 3; i < B_FULL; i++) mbar_init(bar + 8 * i, i == B_XFREE ? 16 : (i >= B_KRDY ? 8 : (i == B_TAB ? 4 : 1)));
          asm volatile("fence.mbarrier_init.release.cluster;" ::: "memory");
          fence_async_smem();
        } else if (warp == 2) {
#pragma unroll
          for (int i = B_FULL; i < B_COUNT; i++) mbar_init(bar + 8 * i, i >= B_EMPTY ? 16 : 1);
          asm volatile("fence.mbarrier_init.release.cluster;" ::: "memory");
          fence_async_smem();
        }
      } else if (warp == 4 && lane < 8) {
        asm volatile("prefetch.tensormap [%0];" ::"l"(&P.tm_wo + (lane - 1)) : "memory");
      }
      __syncwarp();
      const unsigned epoch = S->epoch[(kCtas + cta) * 32 + lane];
      bar_arrive(4, 384);
      asm volatile("barrier.cluster.arrive.relaxed.aligned;" ::: "memory");
      if (wg == 1) bar_arrive(6, 256);
      bar_sync(1, 256);
      tag = next_tag(epoch);
      if (lane < 16) S->st2[gd][16 * (8 * rd + warp) + lane] = make_uint4(0, 0, 0, 0);
      if (warp == 2) S->epoch[(kCtas + cta) * 32 + lane] = tag;
      uint32_t xa[32][4];
      const uint32_t sw = lane & 7, hi = lane >> 4;
      RowNorm n0, n1;
      {
        float ds[2][4] = {}, g0[2][4] = {}, g1[2][4] = {};
        const uint32_t xrow = sb + OFF_WV + (warp * 16 + (lane & 15)) * 128;
        const uint4* mp = reinterpret_cast<const uint4*>(&S->mod1[0][4 * tid]);
        uint4 a[8];
        mbar_wait(bar + 8 * B_X, 0);
#pragma unroll
        for (int k = 0; k < 32; k++) {
          if (k == 16) {
            mbar_wait(bar + 8 * (B_X + 1), 0);
#pragma unroll
            for (int i = 0; i < 8; i++) a[i] = ld_try(mp + i * 256);
          }
          ldsm4(xa[k], xrow + (k >> 2) * 2 * U + (((2 * (k & 3) + hi) ^ sw) << 4));
          mma16816(ds[k & 1], xa[k][0], xa[k][1], xa[k][2], xa[k][3], 0x3F803F80u, 0x3F803F80u);
          mma1688(g0[0], xa[k][0], xa[k][1], xa[k][0]);
          mma1688(g1[0], xa[k][0], xa[k][1], xa[k][1]);
          mma1688(g0[1], xa[k][2], xa[k][3], xa[k][2]);
          mma1688(g1[1], xa[k][2], xa[k][3], xa[k][3]);
        }
        validate<8, 256>(a, mp, tag);
        mbar_wait(bar + 8 * B_M1, 0);
        float v0 = 0.f, v1 = 0.f, v2 = 0.f, v3 = 0.f;
#pragma unroll
        for (int k = 0; k < 8; k++) {
          v0 += __uint_as_float(a[k].x); v1 += __uint_as_float(a[k].y); v2 += __uint_as_float(a[k].z); v3 += __uint_as_float(a[k].w);
        }
        const float add = wg ? 1.f : 0.f;
        const int u = tid & 127;
        const uint32_t td = sb + OFF_TAB + (u >> 2) * 64 + (u & 1) * 32 + ((u >> 1) & 1) * 4 + (wg ? 0 : 8);
        sts32(td, pack2(add + bf_round(v0), add + bf_round(v1)));
        sts32(td + 16, pack2(add + bf_round(v2), add + bf_round(v3)));
        const int dl = (lane & 28) | (gq >> 1);
        const float q0 = __shfl_sync(0xffffffffu, (gq & 1) ? g0[0][1] + g0[1][1] : g0[0][0] + g0[1][0], dl);
        const float q1 = __shfl_sync(0xffffffffu, (gq & 1) ? g1[0][3] + g1[1][3] : g1[0][2] + g1[1][2], dl);
        const float m0 = (ds[0][0] + ds[1][0]) * (1.f / 512.f), m1 = (ds[0][2] + ds[1][2]) * (1.f / 512.f);
        n0 = make_norm(m0, rsqrtf(fmaxf(fmaf(-m0, m0, q0 * (1.f / 512.f)), 0.f) + 1e-5f));
        n1 = make_norm(m1, rsqrtf(fmaxf(fmaf(-m1, m1, q1 * (1.f / 512.f)), 0.f) + 1e-5f));
        asm volatile("barrier.cluster.wait.aligned;" ::: "memory");
        arrive_both(bar + 8 * B_XFREE, lane);
#pragma unroll
        for (int k = 0; k < 8; k++) {
          xa[k][0] = norm1(xa[k][0], n0); xa[k][1] = norm1(xa[k][1], n1);
          xa[k][2] = norm1(xa[k][2], n0); xa[k][3] = norm1(xa[k][3], n1);
        }
        mbar_wait(bar + 8 * B_WKV, 0);
      }
      bar_sync(1, 256);
      const uint32_t trow = sb + (warp * 16 + (lane & 15)) * 128;
      {
        float acc[64];
        uint4 tb[4];
#define MODULATE(K, T)                                                                                                \
  {                                                                                                                   \
    xa[K][0] = hfma2(xa[K][0], (T).x, (T).z); xa[K][1] = hfma2(xa[K][1], (T).x, (T).z);                               \
    xa[K][2] = hfma2(xa[K][2], (T).y, (T).w); xa[K][3] = hfma2(xa[K][3], (T).y, (T).w);                               \
  }
#pragma unroll
        for (int c = 0; c < 4; c++) {
#pragma unroll
          for (int k = 8 * c + (c ? 4 : 0); k < 8 * c + 8; k++) {
            const uint4 t = lds128(sb + OFF_TAB + k * 64 + q * 16);
            MODULATE(k, t);
          }
          if (c > 0) mbar_wait(bar + 8 * (B_WKV + c), 0);
          if (c < 3) {
#pragma unroll
            for (int k = 0; k < 4; k++) tb[k] = lds128(sb + OFF_TAB + (8 * c + 8 + k) * 64 + q * 16);
          }
          bar_sync(6 + wg, 256);
          wg_fence();
#pragma unroll
          for (int k = 0; k < 8; k++)
            wgmma_rs_n128(acc, xa[8 * c + k][0], xa[8 * c + k][1], xa[8 * c + k][2], xa[8 * c + k][3],
                          mkdesc(db + (kv_off(c) >> 4) + ((kv_lbo(c) >> 4) << 16) + k * 128), (c | k) != 0);
          wg_commit();
          wg_wait<1>();
          bar_arrive(7 - wg, 256);
          if (c < 3) {
            const uint32_t after = clock32() & (tag == 0 ? 1u : 0u);
            n0.c ^= after;
            n1.c ^= after;
#pragma unroll
            for (int k = 8 * c + 8; k < 8 * c + 16; k++) {
              xa[k][0] = norm1(xa[k][0], n0); xa[k][1] = norm1(xa[k][1], n1);
              xa[k][2] = norm1(xa[k][2], n0); xa[k][3] = norm1(xa[k][3], n1);
            }
#pragma unroll
            for (int k = 0; k < 4; k++) MODULATE(8 * c + 8 + k, tb[k]);
          }
        }
        wg_wait<0>();
        pin(acc);
        uint4* kdst = &S->kv[cta * 2048 + warp * 128 + lane];
#pragma unroll
        for (int t = 0; t < 8; t++) {
          const uint4 w = make_uint4(pack2(acc[8 * t], acc[8 * t + 1]), pack2(acc[8 * t + 2], acc[8 * t + 3]),
                                     pack2(acc[8 * t + 4], acc[8 * t + 5]), pack2(acc[8 * t + 6], acc[8 * t + 7]) & ~1u);
          st_tag(tag, kdst + (t >> 2) * 1024 + (t & 3) * 32, w);
          stsm4(trow + 4 * U + (t >> 2) * OFF_V + (((2 * (t & 3) + hi) ^ sw) << 4), w.x, w.y, w.z, w.w);
        }
        __syncwarp();
        if (lane == 0) mbar_arrive(bar + 8 * B_KRDY);
      }
      {
        float acc[32];
        const uint4* s2 = &S->kv[r >= 2 ? (cta - 16) * 2048 + warp * 128 + lane : g * 2048 + q];
        const uint4* s1 = &S->kv[r >= 1 ? (cta - 8) * 2048 + warp * 128 + lane : g * 2048 + q];
        uint4 f[4][4];
#pragma unroll
        for (int c = 0; c < 4; c++) {
          if (!(c & 1)) mbar_wait(bar + 8 * (B_WKV + 4 + (c >> 1)), 0);
          wg_fence();
#pragma unroll
          for (int k = 8 * c; k < 8 * c + 8; k++) wgmma_rs_n64(acc, xa[k][0], xa[k][1], xa[k][2], xa[k][3], mkdesc(db + (OFF_WQ >> 4) + k * 128), k > 0);
          wg_commit();
          if (c == 2) {
#pragma unroll
            for (int t = 0; t < 4; t++) { f[0][t] = ld_try(s2 + 32 * t); f[1][t] = ld_try(s1 + 32 * t); }
          }
          if (c == 3) {
            wg_wait<1>();
#pragma unroll
            for (int t = 0; t < 4; t++) { f[2][t] = ld_try(s2 + 1024 + 32 * t); f[3][t] = ld_try(s1 + 1024 + 32 * t); }
          }
        }
        wg_wait<0>();
        pin(acc);
#pragma unroll
        for (int i = 0; i < 16; i++) qf[i] = pack2(acc[2 * i] * kScale, acc[2 * i + 1] * kScale);
        arrive_both(bar + 8 * (B_EMPTY + 5 + (lane >> 1)), lane < 4 ? (lane & 1) : 2);
        mbar_wait(bar + 8 * B_KRDY, 0);
#pragma unroll
        for (int i = 0; i < 4; i++) {
          validate<4, 32>(f[i], ((i & 1) ? s1 : s2) + (i >> 1) * 1024, tag);
          if (r + (i & 1) < 2) {
#pragma unroll
            for (int t = 0; t < 4; t++) f[i][t] = i < 2 ? make_uint4(f[i][t].x, f[i][t].x, f[i][t].z, f[i][t].z) : make_uint4(0, 0, 0, 0);
          }
#pragma unroll
          for (int t = 0; t < 4; t++)
            stsm4(trow + (i & 1) * 2 * U + (i >> 1) * OFF_V + (((2 * t + hi) ^ sw) << 4), f[i][t].x, f[i][t].y, f[i][t].z, f[i][t].w);
          if (i & 1) {
            __syncwarp();
            if (lane == 0) mbar_arrive(bar + 8 * (B_KN + (i >> 1)));
          }
        }
      }
    }
    const int rt = 8 * rd + warp, fo = (rt * 32 + 4 * gd) * 32 + lane;
    const uint4* osrc = &S->o[rt * 32 * 32 + lane];
    uint4 oa[32];
    {
      mbar_wait(bar + 8 * B_KN, 0);
      const int b0 = r >= 2 ? 0 : 16 - 8 * r - warp;
      const bool p0 = 2 * q > gq, p1 = 2 * q + 1 > gq;
      const uint32_t msk = (p0 ? 0xFFFFu : 0u) | (p1 ? 0xFFFF0000u : 0u);
      const uint32_t lm = b0 > 0 ? ~msk : ~0u, lo = b0 > 0 ? 0u : ~0u;
      const uint32_t krow = sb + OFF_K + warp * 2048 + ((lane >> 4) * 8 + (lane & 7)) * 128;
      const uint32_t vrow = sb + OFF_V + warp * 2048 + (lane & 15) * 128;
      uint4* dst = &S->o[((8 * r + warp) * 32 + 4 * g) * 32 + lane];
      const uint32_t kc = (lane >> 3) & 1, vc = lane >> 4, sw = lane & 7;
      const uint32_t ones = 0x3F803F80u;
      const int zero = b0 >> 8;
      uint32_t redo = 0;
      float e[8], n0, n1, po0[4] = {}, po1[4] = {}, pl[4] = {1.f, 1.f, 1.f, 1.f};
      qk_edge(e, qf, krow + ((kc ^ sw) << 4), p0, p1);
      edge_offset(e, -INFINITY, -INFINITY, n0, n1);
      mbar_wait(bar + 8 * B_VN, 0);
#pragma unroll
      for (int k = 0; k < 4; k++) st_tag(tag + 1, &S->h2[fo + 32 * k], make_uint4(0, 0, 0, 0));
#define ON(b) ((b) >= b0 ? ones : 0u)
      auto finish = [&](int h) {
        const float t = ((po0[0] + po0[1]) + (po0[2] + po0[3])) + ((po1[0] + po1[1]) + (po1[2] + po1[3]));
        const bool ok = pl[0] < 1e12f && pl[2] < 1e12f && fabsf(t) <= 3e38f;
        const uint4 w = attn_out(po0, po1, pl);
        st_tag_if(ok && h >= 0, tag, dst + 32 * h, w);
        redo |= ok ? 0u : 1u << h;
        return (w.x ^ w.y) ^ (w.z ^ w.w) ^ redo;
      };
      auto head = [&](int h, auto last_c) {
        constexpr bool LAST = decltype(last_c)::value;
        const uint32_t ka = krow + (((2 * h + kc) ^ sw) << 4), kb = krow + (((2 * h + 2 + kc) ^ sw) << 4);
        const uint32_t va = vrow + (((2 * h + vc) ^ sw) << 4);
        const float cq[4] = {n0, __int_as_float(fi(n0) | zero), n1, __int_as_float(fi(n1) | zero)};
        float s[8], o0[4], o1[4], l[4];
        uint32_t pa[4], h0, h1, kd[17], kcur = ka;
        exp_block(pa, e);
        const uint32_t fin = finish(h - 1);
        h0 = hadd2(pa[0] & lm, pa[2] & lo); h1 = hadd2(pa[1], pa[3] & lm);
        pv_edge(o0, o1, pa, va, msk);
        kd[16] = ka | ((fi(o0[0]) ^ fin) & zero);
        qk_block(s, qf, ka + 15 * 2048, cq);
#pragma unroll
        for (int b = 15; b > 0; b--) {
          exp_block(pa, s);
          if (b <= 13 && (b & 1)) kcur = kd[b + 3];
          if (b > 1) qk_block(s, qf, kcur + (b - 1) * 2048, cq);
          if (LAST && (b == 11 || b == 6 || b == 2)) {
            const int hh = b == 11 ? 0 : (b == 6 ? 1 : 2);
#pragma unroll
            for (int k = 0; k < 8; k++) oa[8 * hh + k] = ld_try(osrc + (4 * k + hh) * 32);
#pragma unroll
            for (int k = 0; k < 8; k++) asm volatile("" : "+f"(s[k]));
            mbar_wait(bar + 8 * (b == 11 ? B_WO : B_TAB), 0);
          }
          if (b == 15) mma16816_z(l, h0, h1, hadd2(pa[0], pa[2]), hadd2(pa[1], pa[3]), ones, ON(b));
          else if (b & 1) mma16816(l, h0, h1, hadd2(pa[0], pa[2]), hadd2(pa[1], pa[3]), ON(b + 1), ON(b));
          else { h0 = hadd2(pa[0], pa[2]); h1 = hadd2(pa[1], pa[3]); }
          pv_block(o0, o1, pa, va + b * 2048);
          kd[b] = ka | (fi(o0[0]) & zero);
          if (!LAST && b == 8) {
            qk_edge(e, qf + 4, kb, p0, p1);
            edge_offset(e, -INFINITY, -INFINITY, n0, n1);
            kd[b] |= (fi(n0) ^ fi(n1)) & zero;
          }
        }
#pragma unroll
        for (int i = 0; i < 4; i++) { po0[i] = o0[i]; po1[i] = o1[i]; pl[i] = l[i]; }
      };
      auto rotate = [&]() {
        const uint32_t t0 = qf[0], t1 = qf[1], t2 = qf[2], t3 = qf[3];
#pragma unroll
        for (int i = 0; i < 12; i++) qf[i] = qf[i + 4];
        qf[12] = t0; qf[13] = t1; qf[14] = t2; qf[15] = t3;
      };
#pragma unroll 1
      for (int h = 0; h < 3; h++) {
        head(h, BoolC<false>());
        rotate();
      }
      head(3, BoolC<true>());
      finish(3);
      if (__any_sync(0xffffffffu, redo != 0)) {
#pragma unroll 1
        for (int h = 0; h < 4; h++) {
          rotate();
          if (!__any_sync(0xffffffffu, (redo >> h) & 1)) continue;
          const uint32_t ka = krow + (((2 * h + kc) ^ sw) << 4), va = vrow + (((2 * h + vc) ^ sw) << 4);
          float s[8], m0 = -INFINITY, m1 = -INFINITY;
          uint32_t pa[4];
#pragma unroll 1
          for (int b = 1; b < 16; b++) {
            const float z[4] = {};
            qk_block(s, qf, ka + b * 2048, z);
            max_block(m0, m1, s);
          }
          qk_edge(e, qf, ka, p0, p1);
          edge_offset(e, m0, m1, n0, n1);
          exp_block(pa, e);
          mma16816_z(pl, pa[0] & lm, pa[1], pa[2] & lo, pa[3] & lm, ones, ones);
          pv_edge(po0, po1, pa, va, msk);
#pragma unroll 1
          for (int b = 1; b < 16; b++) {
            const float cq[4] = {n0, n0, n1, n1};
            qk_block(s, qf, ka + b * 2048, cq);
            exp_block(pa, s);
            mma16816(pl, pa[0], pa[1], pa[2], pa[3], ON(b), ON(b));
            pv_block(po0, po1, pa, va + b * 2048);
          }
          if ((redo >> h) & 1) st_tag(tag, dst + 32 * h, attn_out(po0, po1, pl));
        }
      }
    }
    {
      float acc[32];
      uint32_t xr[4][4], tga[8], tsc[8], tsh[8];
#pragma unroll
      for (int h = 0; h < 4; h++) {
        validate<8, 128>(&oa[8 * h], osrc + 32 * h, tag);
        if (h == 0) {
          fence_async_smem();
          __syncwarp();
          if (lane == 0) mbar_arrive(bar + 8 * B_KRDY);
        }
        if (h == 3) {
          mbar_wait(bar + 8 * B_XR, 0);
#pragma unroll
          for (int k = 0; k < 4; k++) ldsm4(xr[k], sb + OFF_RED + 2 * U + (warp * 16 + (lane & 15)) * 128 + (((2 * k + (lane >> 4)) ^ (lane & 7)) << 4));
#pragma unroll
          for (int t = 0; t < 8; t++) {
            const uint4 tb = lds128(sb + OFF_TMP + (4 * t + q) * 16);
            tga[t] = tb.x; tsh[t] = tb.y; tsc[t] = tb.z;
          }
          arrive_both(bar + 8 * (B_EMPTY + (lane >> 1)), lane < 6 ? (lane & 1) : 2);
        }
        wg_fence();
#pragma unroll
        for (int s = 0; s < 8; s++)
          wgmma_rs_n64(acc, oa[8 * h + s].x, oa[8 * h + s].y, oa[8 * h + s].z, oa[8 * h + s].w, mkdesc(db + (OFF_WV >> 4) + (4 * s + h) * 128), (h | s) != 0);
        if (h == 2) {
#pragma unroll
          for (int i = 24; i < 32; i++) oa[i] = ld_try(osrc + (4 * (i & 7) + 3) * 32);
        }
      }
      wg_commit();
      wg_wait<0>();
      pin(acc);
      float s0 = 0.f, s1 = 0.f;
#pragma unroll
      for (int t = 0; t < 8; t++) {
        const float gl = bf_lo(tga[t]), gh = bf_hi(tga[t]);
        const uint32_t xa = xr[t >> 1][2 * (t & 1)], xb = xr[t >> 1][2 * (t & 1) + 1];
        acc[4 * t] = fmaf(gl, acc[4 * t], bf_lo(xa));
        acc[4 * t + 1] = fmaf(gh, acc[4 * t + 1], bf_hi(xa));
        acc[4 * t + 2] = fmaf(gl, acc[4 * t + 2], bf_lo(xb));
        acc[4 * t + 3] = fmaf(gh, acc[4 * t + 3], bf_hi(xb));
        s0 += acc[4 * t] + acc[4 * t + 1];
        s1 += acc[4 * t + 2] + acc[4 * t + 3];
      }
      s0 += __shfl_xor_sync(0xffffffffu, s0, 1); s1 += __shfl_xor_sync(0xffffffffu, s1, 1);
      s0 += __shfl_xor_sync(0xffffffffu, s0, 2); s1 += __shfl_xor_sync(0xffffffffu, s1, 2);
      s0 *= (1.f / 64.f); s1 *= (1.f / 64.f);
      float q0 = 0.f, q1 = 0.f;
#pragma unroll
      for (int t = 0; t < 8; t++) {
        float d;
        d = acc[4 * t] - s0; q0 = fmaf(d, d, q0);
        d = acc[4 * t + 1] - s0; q0 = fmaf(d, d, q0);
        d = acc[4 * t + 2] - s1; q1 = fmaf(d, d, q1);
        d = acc[4 * t + 3] - s1; q1 = fmaf(d, d, q1);
      }
      q0 += __shfl_xor_sync(0xffffffffu, q0, 1); q1 += __shfl_xor_sync(0xffffffffu, q1, 1);
      q0 += __shfl_xor_sync(0xffffffffu, q0, 2); q1 += __shfl_xor_sync(0xffffffffu, q1, 2);
      if (q < 2) {
        const unsigned long long tg = (unsigned long long)tag << 32;
        st_rlx2(&S->st2[gd][16 * rt + gq + 8 * q], tg | __float_as_uint(q == 0 ? s0 : s1), tg | __float_as_uint(q == 0 ? q0 : q1));
      }
      const uint4* sp = &S->st2[2 * q][16 * rt + gq];
      ulonglong2 ua = ld_rlx2(sp), ub = ld_rlx2(sp + 2048), uc = ld_rlx2(sp + 8), ud = ld_rlx2(sp + 2048 + 8);
#pragma unroll
      for (int k = 0; k < 4; k++) {
        uint32_t xw[4];
#pragma unroll
        for (int i = 0; i < 4; i++) {
          xw[i] = pack2(acc[8 * k + 2 * i], acc[8 * k + 2 * i + 1]);
          acc[8 * k + 2 * i] = bf_lo(xw[i]);
          acc[8 * k + 2 * i + 1] = bf_hi(xw[i]);
        }
        asm volatile("st.shared.v4.u32 [%0], {%1,%2,%3,%4};" ::"r"(sb + OFF_RED + k * 4096 + tid * 16), "r"(xw[0]), "r"(xw[1]), "r"(xw[2]), "r"(xw[3]) : "memory");
      }
      pin(acc);
      int n = 0;
      while (__any_sync(0xffffffffu, !(tag_ok(ua, tag) && tag_ok(ub, tag) && tag_ok(uc, tag) && tag_ok(ud, tag))) && ++n < kSpinLimit) {
        ua = ld_rlx2(sp); ub = ld_rlx2(sp + 2048); uc = ld_rlx2(sp + 8); ud = ld_rlx2(sp + 2048 + 8);
      }
      const float ma = lo_f(ua.x), mb = lo_f(ub.x), mc = lo_f(uc.x), md = lo_f(ud.x);
      float m0 = ma + mb, m1 = mc + md;
      m0 += __shfl_xor_sync(0xffffffffu, m0, 1); m1 += __shfl_xor_sync(0xffffffffu, m1, 1);
      m0 += __shfl_xor_sync(0xffffffffu, m0, 2); m1 += __shfl_xor_sync(0xffffffffu, m1, 2);
      m0 *= 0.125f; m1 *= 0.125f;
      float v0 = 64.f * ((ma - m0) * (ma - m0) + (mb - m0) * (mb - m0)) + lo_f(ua.y) + lo_f(ub.y);
      float v1 = 64.f * ((mc - m1) * (mc - m1) + (md - m1) * (md - m1)) + lo_f(uc.y) + lo_f(ud.y);
      v0 += __shfl_xor_sync(0xffffffffu, v0, 1); v1 += __shfl_xor_sync(0xffffffffu, v1, 1);
      v0 += __shfl_xor_sync(0xffffffffu, v0, 2); v1 += __shfl_xor_sync(0xffffffffu, v1, 2);
      const float r0 = rsqrtf(v0 * (1.f / 512.f) + 1e-5f), r1 = rsqrtf(v1 * (1.f / 512.f) + 1e-5f);
      const float c0 = -m0 * r0, c1 = -m1 * r1;
      uint32_t hw[16];
#pragma unroll
      for (int i = 0; i < 16; i++) {
        const float rs = (i & 1) ? r1 : r0, cs = (i & 1) ? c1 : c0;
        hw[i] = hfma2(pack2(fmaf(acc[2 * i], rs, cs), fmaf(acc[2 * i + 1], rs, cs)), tsc[i >> 1], tsh[i >> 1]);
      }
#pragma unroll
      for (int k = 0; k < 4; k++) st_tag(tag, &S->h2[fo + 32 * k], make_uint4(hw[4 * k], hw[4 * k + 1], hw[4 * k + 2], hw[4 * k + 3]));
    }
    const uint4* hsrc = &S->hh[(rt * 86 + 44 * rank) * 32 + lane];
    uint4 a[4][8], x1[4];
#define DN_VALIDATE(T)                                                                                                \
  {                                                                                                                   \
    uint4* av = a[(T) & 3];                                                                                           \
    if ((T) < 4) {                                                                                                    \
      validate<4, 32>(av, hsrc + dn_step(T, 0) * 32, tag);                                                            \
      validate<4, 32>(av + 4, hsrc + dn_step(T, 4) * 32, tag);                                                        \
    } else {                                                                                                          \
      validate<3, 32>(av, hsrc + dn_step(T, 0) * 32, tag);                                                            \
      validate<3, 32>(av + 4, hsrc + dn_step(T, 4) * 32, tag);                                                        \
    }                                                                                                                 \
  }
    {
      const int rg = 8 * r + warp;
      const uint4* src = &S->h2[rg * 32 * 32 + lane];
      uint4 xa[32];
      {
#pragma unroll
        for (int k = 0; k < 8; k++) xa[k] = ld_try(src + 32 * k);
        validate<8, 32>(&xa[0], src, tag);
#pragma unroll
        for (int k = 8; k < 16; k++) xa[k] = ld_try(src + 32 * k);
      }
      arrive_both(bar + 8 * (B_EMPTY + 3 + (lane >> 1)), lane < 4 ? (lane & 1) : 2);
      const uint32_t dg = db + ((16384 >> 4) << 16);
      uint4* dst = &S->hh[(rg * 86 + 11 * g) * 32 + lane];
#define HH_OUT(G, U, K, OFFS)                                                                                         \
  st_tag(tag, dst + (OFFS) + 32 * (K),                                                                                \
         make_uint4(pack2((G)[8 * (K)] * (U)[8 * (K)], (G)[8 * (K) + 1] * (U)[8 * (K) + 1]),                          \
                    pack2((G)[8 * (K) + 2] * (U)[8 * (K) + 2], (G)[8 * (K) + 3] * (U)[8 * (K) + 3]),                  \
                    pack2((G)[8 * (K) + 4] * (U)[8 * (K) + 4], (G)[8 * (K) + 5] * (U)[8 * (K) + 5]),                  \
                    pack2((G)[8 * (K) + 6] * (U)[8 * (K) + 6], (G)[8 * (K) + 7] * (U)[8 * (K) + 7])))
#define GU_TURN(ACC, FN, C, T)                                                                                        \
  {                                                                                                                   \
    const int slot = ring_slot(T);                                                                                    \
    const uint32_t d = dg + slot * (STAGE >> 4);                                                                      \
    mbar_wait(bar + 8 * (B_FULL + slot), (T) >= 6);                                                                   \
    bar_sync(6 + wg, 256);                                                                                            \
    wg_fence();                                                                                                       \
    _Pragma("unroll") for (int k = 0; k < 8; k++)                                                                     \
      FN(ACC, xa[8 * (C) + k].x, xa[8 * (C) + k].y, xa[8 * (C) + k].z, xa[8 * (C) + k].w, mkdesc(d + k * 128), ((C) | k) != 0); \
    wg_commit();                                                                                                      \
    bar_arrive(7 - wg, 256);                                                                                          \
    if ((C) > 0) {                                                                                                    \
      wg_wait<1>();                                                                                                   \
      arrive_both(bar + 8 * (B_EMPTY + ring_slot((T) - 1)), lane);                                                    \
    }                                                                                                                 \
  }
#define GU_END(ACC, T)                                                                                                \
  {                                                                                                                   \
    wg_wait<0>();                                                                                                     \
    pin(ACC);                                                                                                         \
    arrive_both(bar + 8 * (B_EMPTY + ring_slot(T)), lane);                                                            \
  }
#pragma unroll 1
      for (int p = 0; p < 2; p++) {
        float acc[64];
#pragma unroll
        for (int c = 0; c < 4; c++) {
          GU_TURN(acc, wgmma_rs_n128, c, 4 * p + c);
          if (p == 0 && c < 3) validate<8, 32>(&xa[8 * c + 8], src + 256 * c + 256, tag);
          if (p == 0 && c < 2) {
#pragma unroll
            for (int k = 16 + 8 * c; k < 24 + 8 * c; k++) xa[k] = ld_try(src + 32 * k);
          }
        }
        GU_END(acc, 4 * p + 3);
#pragma unroll
        for (int k = 0; k < 4; k++) HH_OUT(acc, acc + 32, k, 128 * p);
      }
      {
        float ag[24], au[24];
        auto mma48 = [&](int, uint32_t a0, uint32_t a1, uint32_t a2, uint32_t a3, uint64_t d, bool acc) {
          wgmma_rs_n48(ag, a0, a1, a2, a3, d, acc);
          wgmma_rs_n48(au, a0, a1, a2, a3, d + 1024, acc);
        };
#pragma unroll
        for (int c = 0; c < 4; c++) {
          GU_TURN(0, mma48, c, 8 + c);
          if (c == 3) DN_VALIDATE(0);
          if (c > 0) {
#pragma unroll
            for (int e = 0; e < 8; e++) a[c - 1][e] = ld_try(hsrc + dn_step(c - 1, e) * 32);
          }
        }
        GU_END(ag, 11);
        pin(au);
#pragma unroll
        for (int k = 0; k < 3; k++)
          if (k == 0 || g != 7) HH_OUT(ag, au, k, 256);
      }
    }
    {
      const uint4* src = hsrc;
      float keep[32], send[32];
      const uint32_t dd = db + ((8192 >> 4) << 16);
#define DN_HALF(ACC, OFFS, T)                                                                                         \
  _Pragma("unroll") for (int e = 0; e < 8; e++)                                                                       \
    if ((T) < 4 || (e & 3) != 3)                                                                                      \
      wgmma_rs_n64(ACC, a[(T) & 3][e].x, a[(T) & 3][e].y, a[(T) & 3][e].z, a[(T) & 3][e].w,                           \
                   mkdesc(dd + ring_slot(T) * (STAGE >> 4) + (OFFS) + (e >> 2) * 1024 + (e & 3) * 128), true);
#pragma unroll
      for (int t = 0; t < 3; t++) {
        uint4* at = a[t];
        const uint32_t d = dd + ring_slot(t) * (STAGE >> 4);
        mbar_wait(bar + 8 * (B_FULL + ring_slot(t)), 0);
        bar_sync(6 + wg, 256);
        wg_fence();
#pragma unroll
        for (int e = 0; e < 8; e++) {
          wgmma_rs_n64(keep, at[e].x, at[e].y, at[e].z, at[e].w, mkdesc(d + (e >> 2) * 1024 + (e & 3) * 128), (t | e) != 0);
          wgmma_rs_n64(send, at[e].x, at[e].y, at[e].z, at[e].w, mkdesc(d + 512 + (e >> 2) * 1024 + (e & 3) * 128), (t | e) != 0);
        }
        wg_commit();
        bar_arrive(7 - wg, 256);
        DN_VALIDATE(t + 1);
        wg_wait<1>();
        uint4* an = a[(t + 3) & 3];
#pragma unroll
        for (int e = 0; e < 8; e++)
          if (t == 0 || (e & 3) != 3) an[e] = ld_try(src + dn_step(t + 3, e) * 32);
        if (t == 0) {
#pragma unroll
          for (int e = 0; e < 4; e++) x1[e] = lds128(sb + OFF_RED + e * 4096 + tid * 16);
          arrive_both(bar + 8 * (B_EMPTY + 2), lane + (int)((x1[0].x ^ x1[1].x ^ x1[2].x ^ x1[3].x) == 0x12345u && tag == 0) * 32);
        }
      }
      mbar_wait(bar + 8 * (B_FULL + ring_slot(3)), 0);
      mbar_wait(bar + 8 * (B_FULL + ring_slot(4)), 0);
      mbar_wait(bar + 8 * (B_FULL + ring_slot(5)), 0);
      mbar_wait(bar + 8 * (B_EMPTY + 2), 1);
      bar_sync(6 + wg, 256);
      wg_fence();
      DN_HALF(send, 512, 3);
      DN_VALIDATE(4);
      DN_VALIDATE(5);
      wg_fence();
      DN_HALF(send, 512, 4);
      DN_HALF(send, 512, 5);
      wg_commit();
      bar_arrive(7 - wg, 256);
      wg_wait<0>();
      pin(send);
      uint32_t rbar;
      asm volatile("mapa.shared::cluster.u32 %0, %1, %2;" : "=r"(rbar) : "r"(bar), "r"(rank ^ 1));
      const uint32_t roff = OFF_RED + warp * 4096 + lane * 16;
      const uint32_t rbuf = rbar - OFF_BAR + roff, rb = rbar + 8 * (B_RED + wg);
#pragma unroll
      for (int i = 0; i < 8; i++)
        asm volatile("st.async.weak.shared::cluster.mbarrier::complete_tx::bytes.v4.f32 [%0], {%1,%2,%3,%4}, [%5];" ::"r"(rbuf + i * 512),
                     "f"(send[4 * i]), "f"(send[4 * i + 1]), "f"(send[4 * i + 2]), "f"(send[4 * i + 3]), "r"(rb) : "memory");
      wg_fence();
      DN_HALF(keep, 0, 3);
      DN_HALF(keep, 0, 4);
      DN_HALF(keep, 0, 5);
      wg_commit();
      wg_wait<0>();
      pin(keep);
      mbar_wait_cluster(bar + 8 * (B_RED + wg), 0);
      uint32_t ow[16];
#pragma unroll
      for (int t = 0; t < 8; t++) {
        const uint4 o = lds128(sb + roff + t * 512);
        const uint32_t gb = lds32(sb + OFF_TMP + (4 * t + q) * 16 + 12);
        const float gl = bf_lo(gb), gh = bf_hi(gb);
        const uint32_t xa = (t & 1) ? x1[t >> 1].z : x1[t >> 1].x, xb = (t & 1) ? x1[t >> 1].w : x1[t >> 1].y;
        ow[2 * t] = pack2(fmaf(gl, keep[4 * t] + __uint_as_float(o.x), bf_lo(xa)), fmaf(gh, keep[4 * t + 1] + __uint_as_float(o.y), bf_hi(xa)));
        ow[2 * t + 1] = pack2(fmaf(gl, keep[4 * t + 2] + __uint_as_float(o.z), bf_lo(xb)), fmaf(gh, keep[4 * t + 3] + __uint_as_float(o.w), bf_hi(xb)));
      }
      const uint32_t patch = sb + OFF_RED + warp * 4096;
      __syncwarp();
#pragma unroll
      for (int t = 0; t < 4; t++)
        stsm4(patch + (lane & 15) * 128 + (((2 * t + (lane >> 4)) ^ (lane & 7)) << 4), ow[4 * t], ow[4 * t + 1], ow[4 * t + 2], ow[4 * t + 3]);
      __syncwarp();
      __nv_bfloat16* op = gout + (size_t)(16 * rt + (lane >> 3)) * kD + 64 * gd + (lane & 7) * 8;
#pragma unroll
      for (int t = 0; t < 4; t++) {
        const int row = 4 * t + (lane >> 3);
        asm volatile("" ::: "memory");
        *reinterpret_cast<uint4*>(op + 4 * t * kD) = lds128(patch + row * 128 + (((lane & 7) ^ (row & 7)) << 4));
      }
    }
  }
}

typedef CUresult (*EncodeFn)(CUtensorMap*, CUtensorMapDataType, cuuint32_t, void*, const cuuint64_t*, const cuuint64_t*, const cuuint32_t*,
                             const cuuint32_t*, CUtensorMapInterleave, CUtensorMapSwizzle, CUtensorMapL2promotion, CUtensorMapFloatOOBfill);

void encode(EncodeFn fn, CUtensorMap* tm, const void* base, int rank, const cuuint64_t* dims, const cuuint64_t* strides, const cuuint32_t* box) {
  const cuuint32_t es[5] = {1, 1, 1, 1, 1};
  CUresult rc = fn(tm, CU_TENSOR_MAP_DATA_TYPE_BFLOAT16, rank, const_cast<void*>(base), dims, strides, box, es, CU_TENSOR_MAP_INTERLEAVE_NONE,
                   CU_TENSOR_MAP_SWIZZLE_128B, CU_TENSOR_MAP_L2_PROMOTION_L2_128B, CU_TENSOR_MAP_FLOAT_OOB_FILL_NONE);
  (void)rc;
}

}

extern "C" void kernel_launch(void* const* d_in, const int* in_sizes, int n_in, void* d_out, int out_size) {
  (void)in_sizes; (void)n_in; (void)out_size;
  static EncodeFn fn = nullptr;
  static Scratch* scratch = nullptr;
  if (!fn) {
    void* p = nullptr;
    cudaDriverEntryPointQueryResult qr;
    cudaGetDriverEntryPoint("cuTensorMapEncodeTiled", &p, cudaEnableDefault, &qr);
    fn = (EncodeFn)p;
    cudaGetSymbolAddress((void**)&scratch, g_s);
    cudaFuncSetAttribute(fused_block_kernel, cudaFuncAttributeMaxDynamicSharedMemorySize, SMEM_BYTES);
  }
  Params P;
  const __nv_bfloat16* x = (const __nv_bfloat16*)d_in[0];
  const __nv_bfloat16* wqkv = (const __nv_bfloat16*)d_in[1];
  P.wo = (const __nv_bfloat16*)d_in[2];
  P.wg = (const __nv_bfloat16*)d_in[4];
  P.wu = (const __nv_bfloat16*)d_in[5];
  P.wd = (const __nv_bfloat16*)d_in[6];
  {
    const cuuint64_t dims[2] = {1536, 512};
    const cuuint64_t str[1] = {3072};
    const cuuint32_t box[2] = {64, 128};
    encode(fn, &P.tm_qkv, wqkv, 2, dims, str, box);
    const cuuint64_t dimx[2] = {512, 2048};
    const cuuint64_t strx[1] = {1024};
    encode(fn, &P.tm_x, x, 2, dimx, strx, box);
  }
  {
    const cuuint64_t dims[2] = {512, 512};
    const cuuint64_t str[1] = {1024};
    const cuuint32_t box[2] = {64, 256};
    encode(fn, &P.tm_wo, P.wo, 2, dims, str, box);
  }
  {
    const cuuint64_t dims0[3] = {176, 7, 512}, dims1[3] = {144, 1, 512};
    const cuuint64_t str[2] = {352, 2 * kF};
    const cuuint32_t box[3] = {64, 1, 128};
    encode(fn, &P.tm_g0, P.wg, 3, dims0, str, box);
    encode(fn, &P.tm_u0, P.wu, 3, dims0, str, box);
    encode(fn, &P.tm_g1, P.wg + 7 * 176, 3, dims1, str, box);
    encode(fn, &P.tm_u1, P.wu + 7 * 176, 3, dims1, str, box);
  }
  {
    const cuuint64_t dims[2] = {512, kF};
    const cuuint64_t str[1] = {1024};
    const cuuint32_t box[2] = {64, 64};
    encode(fn, &P.tm_wd, P.wd, 2, dims, str, box);
    const cuuint32_t box48[2] = {64, 48};
    encode(fn, &P.tm_wd48, P.wd, 2, dims, str, box48);
  }
  fused_block_kernel<<<kCtas, kThreads, SMEM_BYTES>>>(scratch, x, (const __nv_bfloat16*)d_in[8], (const __nv_bfloat16*)d_in[7], (__nv_bfloat16*)d_out, P);
}
```
